```python
import torch

def _softmax(x, axis=-1):
    return torch.softmax(x, dim=axis)
def _gelu(x):
    return torch.nn.functional.gelu(x, approximate="tanh")
def _silu(x):
    return torch.nn.functional.silu(x)
def _sigmoid(x):
    return torch.sigmoid(x)
def _layernorm(x, axis=-1, eps=1e-5):
    m = x.mean(dim=axis, keepdim=True)
    v = x.var(dim=axis, keepdim=True, unbiased=False)
    return (x - m) / torch.sqrt(v + eps)
def _scatter_add(tgt, idx, src, axis=0):
    return tgt.clone().index_add_(axis, idx, src)
def _segment_sum(src, seg, n):
    out = torch.zeros((n,) + src.shape[1:], dtype=src.dtype)
    return out.index_add_(0, seg, src)
def _pad(x, pw):
    flat = tuple(v for pair in reversed(pw) for v in pair)
    return torch.nn.functional.pad(x, flat)

kernel_name = 'sequential_preLN__compressed_kv_cla__mixer_s_mlp__prompt'

def setup_inputs():

    _w = (lambda a: (lambda t: t.to(torch.bfloat16) if t.is_floating_point() else t)(torch.as_tensor(a)))
    def _A_setup():
        B, H, Sq, Sk, D, M = 1, 32, 2048, 2048, 128, 512
        Dc = 4 * D
        return {
            "x": _w((lambda *s: torch.randn(*s, dtype=torch.bfloat16) * 0.1)(B, Sq, M)),
            "c_kv": _w((lambda *s: torch.randn(*s, dtype=torch.bfloat16) * 0.8)(B, Sk, Dc)),
            "w_q": _w((lambda *s: torch.randn(*s, dtype=torch.bfloat16) * 1.6)(M, H, D) * (M ** -0.5)),
            "w_uk": _w((lambda *s: torch.randn(*s, dtype=torch.bfloat16) * 1.6)(Dc, H, D) * (Dc ** -0.5)),
            "w_uv": _w((lambda *s: torch.randn(*s, dtype=torch.bfloat16) * 0.8)(Dc, H, D) * (Dc ** -0.5)),
            "w_o": _w((lambda *s: torch.randn(*s, dtype=torch.bfloat16) * 0.8)(H, D, M) * ((H * D) ** -0.5)),
        }
    _A_in = _A_setup()

    def _B_setup():
        B, S, D, F = 1, 2048, 512, 1792
        return {
            "x":  _w((lambda *s: torch.randn(*s, dtype=torch.bfloat16) * 0.1)(B, S, D)),
            "w1": _w((lambda *s: torch.randn(*s, dtype=torch.bfloat16) * 3.2)(D, D) * (D ** -0.5)),
            "w2": _w((lambda *s: torch.randn(*s, dtype=torch.bfloat16) * 3.2)(D, D) * (D ** -0.5)),
            "w3": _w((lambda *s: torch.randn(*s, dtype=torch.bfloat16) * 3.2)(D, F) * (D ** -0.5)),
            "w4": _w((lambda *s: torch.randn(*s, dtype=torch.bfloat16) * 3.2)(F, D) * (F ** -0.5)),
        }
    _B_in = _B_setup()

    return {
        "A_x": _A_in["x"],
        "A_c_kv": _A_in["c_kv"],
        "A_w_q": _A_in["w_q"],
        "A_w_uk": _A_in["w_uk"],
        "A_w_uv": _A_in["w_uv"],
        "A_w_o": _A_in["w_o"],
        "B_x": _B_in["x"],
        "B_w1": _B_in["w1"],
        "B_w2": _B_in["w2"],
        "B_w3": _B_in["w3"],
        "B_w4": _B_in["w4"],
    }

def reference(A_x, A_c_kv, A_w_q, A_w_uk, A_w_uv, A_w_o, B_x, B_w1, B_w2, B_w3, B_w4):
    def _A_ref(x, c_kv, w_q, w_uk, w_uv, w_o):
        B, Sq, M = x.shape[0], x.shape[1], x.shape[2]
        Sk = c_kv.shape[1]
        H, D = w_q.shape[1], w_q.shape[2]
        q = torch.einsum("bqm,mhd->bhqd", x, w_q)
        k = torch.einsum("bkc,chd->bhkd", c_kv, w_uk)
        v = torch.einsum("bkc,chd->bhkd", c_kv, w_uv)
        scores = torch.einsum("bhqd,bhkd->bhqk", q, k) * (D ** -0.5)
        off = Sk - Sq
        qi = torch.arange(Sq)[:, None]
        kj = torch.arange(Sk)[None, :]
        cmask = kj <= (qi + off)
        scores = torch.where(cmask[None, None], scores, -1e9)
        p = _softmax(scores, axis=-1)
        ctx = torch.einsum("bhqk,bhkd->bhqd", p, v)
        return torch.einsum("bhqd,hdm->bqm", ctx, w_o)

    def _B_ref(x, w1, w2, w3, w4):
        B, S, D = x.shape
        h = _gelu(_layernorm(x, axis=-1) @ w1)
        c = D // 4
        g0 = _pad(h[:, :, 0*c:1*c], ((0, 0), (1, 0), (0, 0)))[:, :S, :]
        g1 = _pad(h[:, :, 1*c:2*c], ((0, 0), (0, 1), (0, 0)))[:, 1:, :]
        g2 = _pad(h[:, :, 2*c:3*c], ((0, 0), (2, 0), (0, 0)))[:, :S, :]
        g3 = _pad(h[:, :, 3*c:   ], ((0, 0), (0, 2), (0, 0)))[:, 2:, :]
        hs = torch.concatenate([g0, g1, g2, g3], axis=-1) @ w2
        x1 = x + hs
        h2 = _gelu(_layernorm(x1, axis=-1) @ w3) @ w4
        return x1 + h2

    x = A_x
    h = x + _A_ref(_layernorm(x, axis=-1), A_c_kv, A_w_q, A_w_uk, A_w_uv, A_w_o)
    h2 = h + _B_ref(_layernorm(h, axis=-1), B_w1, B_w2, B_w3, B_w4)
    return h2
```

```cpp
#include <cuda_runtime.h>
#include <cuda_bf16.h>
#include <cuda.h>
#include <stdint.h>

typedef __nv_bfloat16 bf16;

constexpr int S_LEN = 2048;
constexpr int DM    = 512;
constexpr int NH    = 32;
constexpr int HD    = 128;
constexpr int FF    = 1792;
constexpr float LN_EPS = 1e-5f;

#define GTS_DECL
#define GTS()
#define PROF_DECL
#define PROF_TS(slot)
#define TL_START(k)
#define TL_MARK(k)
#define TL_END(k)
#define SPIN_LIMIT (1u << 20)

__device__ __forceinline__ uint32_t smem_u32(const void* p) { return (uint32_t)__cvta_generic_to_shared(p); }
__device__ __forceinline__ uint32_t elect_one() {
    uint32_t pred;
    asm volatile("{\n.reg .pred px;\nelect.sync _|px, 0xFFFFFFFF;\nselp.u32 %0, 1, 0, px;\n}\n" : "=r"(pred));
    return pred;
}
__device__ __forceinline__ void mbar_init(uint32_t bar, uint32_t count) {
    asm volatile("mbarrier.init.shared::cta.b64 [%0], %1;" :: "r"(bar), "r"(count) : "memory");
}
__device__ __forceinline__ void mbar_expect_tx(uint32_t bar, uint32_t bytes) {
    asm volatile("mbarrier.arrive.expect_tx.shared::cta.b64 _, [%0], %1;" :: "r"(bar), "r"(bytes) : "memory");
}
__device__ __forceinline__ void mbar_arrive(uint32_t bar) {
    asm volatile("mbarrier.arrive.shared::cta.b64 _, [%0];" :: "r"(bar) : "memory");
}
__device__ __forceinline__ void mbar_arrive_if(uint32_t bar, uint32_t flag) {
    asm volatile("{\n.reg .pred p;\nsetp.ne.b32 p, %1, 0;\n@p mbarrier.arrive.shared::cta.b64 _, [%0];\n}" :: "r"(bar), "r"(flag) : "memory");
}
__device__ __forceinline__ void mbar_arrive_cta(uint32_t bar, uint32_t cta) {
    asm volatile("{\n.reg .b32 ra;\nmapa.shared::cluster.u32 ra, %0, %1;\n"
                 "mbarrier.arrive.shared::cluster.b64 _, [ra];\n}" :: "r"(bar), "r"(cta) : "memory");
}
__device__ __forceinline__ bool mbar_try_wait(uint32_t bar, uint32_t parity) {
    uint32_t ok;
    asm volatile("{\n.reg .pred p;\nmbarrier.try_wait.parity.shared::cta.b64 p, [%1], %2;\nselp.u32 %0, 1, 0, p;\n}"
                 : "=r"(ok) : "r"(bar), "r"(parity) : "memory");
    return ok;
}
__device__ __forceinline__ bool mbar_test(uint32_t bar, uint32_t parity) {
    uint32_t ok;
    asm volatile("{\n.reg .pred p;\nmbarrier.test_wait.parity.shared::cta.b64 p, [%1], %2;\nselp.u32 %0, 1, 0, p;\n}"
                 : "=r"(ok) : "r"(bar), "r"(parity) : "memory");
    return ok;
}
__device__ __forceinline__ void mbar_wait(uint32_t bar, uint32_t parity) {
    uint32_t n = 0;
    while (!mbar_try_wait(bar, parity) && ++n < SPIN_LIMIT) { }
}
__device__ __forceinline__ bool mbar_try_wait_cl(uint32_t bar, uint32_t parity) {
    uint32_t ok;
    asm volatile("{\n.reg .pred p;\nmbarrier.try_wait.parity.shared::cta.b64 p, [%1], %2;\nselp.u32 %0, 1, 0, p;\n}"
                 : "=r"(ok) : "r"(bar), "r"(parity) : "memory");
    return ok;
}
__device__ __forceinline__ void mbar_wait_cl(uint32_t bar, uint32_t parity) {
    uint32_t n = 0;
    while (!mbar_try_wait_cl(bar, parity) && ++n < SPIN_LIMIT) { }
}
__device__ __forceinline__ void fence_mbar_init() { asm volatile("fence.mbarrier_init.release.cluster;" ::: "memory"); }
__device__ __forceinline__ void fence_proxy_async() { asm volatile("fence.proxy.async.shared::cta;" ::: "memory"); }
__device__ __forceinline__ void fence_proxy_async_all() { asm volatile("fence.proxy.async;" ::: "memory"); }

__device__ __forceinline__ void tma_load_2d(uint32_t dst, const CUtensorMap* map, uint32_t bar, int c0, int c1) {
    asm volatile("cp.async.bulk.tensor.2d.shared::cluster.global.mbarrier::complete_tx::bytes [%0], [%1, {%3, %4}], [%2];"
        :: "r"(dst), "l"(map), "r"(bar), "r"(c0), "r"(c1) : "memory");
}
__device__ __forceinline__ void tma_load_3d(uint32_t dst, const CUtensorMap* map, uint32_t bar, int c0, int c1, int c2) {
    asm volatile("cp.async.bulk.tensor.3d.shared::cluster.global.mbarrier::complete_tx::bytes [%0], [%1, {%3, %4, %5}], [%2];"
        :: "r"(dst), "l"(map), "r"(bar), "r"(c0), "r"(c1), "r"(c2) : "memory");
}
__device__ __forceinline__ void tma_load_2d_mc(uint32_t dst, const CUtensorMap* map, uint32_t bar, int c0, int c1, uint16_t mask) {
    asm volatile("cp.async.bulk.tensor.2d.shared::cluster.global.mbarrier::complete_tx::bytes.multicast::cluster [%0], [%1, {%3, %4}], [%2], %5;"
        :: "r"(dst), "l"(map), "r"(bar), "r"(c0), "r"(c1), "h"(mask) : "memory");
}
__device__ __forceinline__ void tma_load_3d_mc(uint32_t dst, const CUtensorMap* map, uint32_t bar, int c0, int c1, int c2, uint16_t mask) {
    asm volatile("cp.async.bulk.tensor.3d.shared::cluster.global.mbarrier::complete_tx::bytes.multicast::cluster [%0], [%1, {%3, %4, %5}], [%2], %6;"
        :: "r"(dst), "l"(map), "r"(bar), "r"(c0), "r"(c1), "r"(c2), "h"(mask) : "memory");
}
__device__ __forceinline__ void tma_store_2d(const CUtensorMap* map, uint32_t src, int c0, int c1) {
    asm volatile("cp.async.bulk.tensor.2d.global.shared::cta.bulk_group [%0, {%2, %3}], [%1];"
        :: "l"(map), "r"(src), "r"(c0), "r"(c1) : "memory");
}
__device__ __forceinline__ void tma_store_2d_hint(const CUtensorMap* map, uint32_t src, int c0, int c1, uint64_t pol) {
    asm volatile("cp.async.bulk.tensor.2d.global.shared::cta.bulk_group.L2::cache_hint [%0, {%2, %3}], [%1], %4;"
        :: "l"(map), "r"(src), "r"(c0), "r"(c1), "l"(pol) : "memory");
}
__device__ __forceinline__ uint64_t policy_evict_first() {
    uint64_t p; asm volatile("createpolicy.fractional.L2::evict_first.b64 %0, 1.0;" : "=l"(p)); return p;
}
__device__ __forceinline__ void tma_store_3d(const CUtensorMap* map, uint32_t src, int c0, int c1, int c2) {
    asm volatile("cp.async.bulk.tensor.3d.global.shared::cta.bulk_group [%0, {%2, %3, %4}], [%1];"
        :: "l"(map), "r"(src), "r"(c0), "r"(c1), "r"(c2) : "memory");
}
__device__ __forceinline__ void tma_red_add_2d(const CUtensorMap* map, uint32_t src, int c0, int c1) {
    asm volatile("cp.reduce.async.bulk.tensor.2d.global.shared::cta.add.bulk_group [%0, {%2, %3}], [%1];"
        :: "l"(map), "r"(src), "r"(c0), "r"(c1) : "memory");
}
__device__ __forceinline__ void tma_prefetch_2d(const CUtensorMap* map, int c0, int c1) {
    asm volatile("cp.async.bulk.prefetch.tensor.2d.L2.global [%0, {%1, %2}];" :: "l"(map), "r"(c0), "r"(c1) : "memory");
}
__device__ __forceinline__ void l2_prefetch(const void* p, uint32_t bytes) {
    asm volatile("cp.async.bulk.prefetch.L2.global [%0], %1;" :: "l"(p), "r"(bytes) : "memory");
}
__device__ __forceinline__ void prefetch_l2(const void* p) { asm volatile("prefetch.global.L2 [%0];" :: "l"(p)); }
__device__ __forceinline__ void tma_commit() { asm volatile("cp.async.bulk.commit_group;" ::: "memory"); }
template<int N> __device__ __forceinline__ void tma_wait_read() { asm volatile("cp.async.bulk.wait_group.read %0;" :: "n"(N) : "memory"); }
template<int N> __device__ __forceinline__ void tma_wait() { asm volatile("cp.async.bulk.wait_group %0;" :: "n"(N) : "memory"); }
__device__ __forceinline__ void prefetch_tmap(const CUtensorMap* map) {
    asm volatile("prefetch.tensormap [%0];" :: "l"(map) : "memory");
}

__device__ __forceinline__ void wgmma_fence() { asm volatile("wgmma.fence.sync.aligned;" ::: "memory"); }
__device__ __forceinline__ void wgmma_commit() { asm volatile("wgmma.commit_group.sync.aligned;" ::: "memory"); }
template<int N> __device__ __forceinline__ void wgmma_wait() { asm volatile("wgmma.wait_group.sync.aligned %0;" :: "n"(N) : "memory"); }

template<int N> __device__ __forceinline__ void fence_regs(float (&d)[N]) {
    #pragma unroll
    for (int i = 0; i < N; i++) asm volatile("" : "+f"(d[i]) :: "memory");
}
template<int N> __device__ __forceinline__ void fence_regs(uint32_t (&d)[N]) {
    #pragma unroll
    for (int i = 0; i < N; i++) asm volatile("" : "+r"(d[i]) :: "memory");
}

__device__ __forceinline__ uint64_t make_desc(uint32_t addr, uint32_t lbo_bytes, uint32_t sbo_bytes) {
    uint64_t d = 0;
    d |= (uint64_t)((addr & 0x3FFFF) >> 4);
    d |= (uint64_t)((lbo_bytes & 0x3FFFF) >> 4) << 16;
    d |= (uint64_t)((sbo_bytes & 0x3FFFF) >> 4) << 32;
    d |= (uint64_t)1 << 62;
    return d;
}
__device__ __forceinline__ uint64_t desc_add(uint64_t d, uint32_t bytes) {
    return d + (uint64_t)(bytes >> 4);
}

__device__ __forceinline__ void bar_sync(int id, int n) { asm volatile("bar.sync %0, %1;" :: "r"(id), "r"(n) : "memory"); }
__device__ __forceinline__ void bar_arrive(int id, int n) { asm volatile("bar.arrive %0, %1;" :: "r"(id), "r"(n) : "memory"); }
__device__ __forceinline__ bool bar_red_or(int id, int n, bool v) {
    uint32_t r;
    asm volatile("{\n.reg .pred p, q;\nsetp.ne.u32 q, %3, 0;\nbar.red.or.pred p, %1, %2, q;\nselp.u32 %0, 1, 0, p;\n}"
                 : "=r"(r) : "r"(id), "r"(n), "r"((uint32_t)v) : "memory");
    return r;
}
template<int R> __device__ __forceinline__ void reg_alloc() { asm volatile("setmaxnreg.inc.sync.aligned.u32 %0;" :: "n"(R)); }
template<int R> __device__ __forceinline__ void reg_dealloc() { asm volatile("setmaxnreg.dec.sync.aligned.u32 %0;" :: "n"(R)); }
__device__ __forceinline__ uint32_t cluster_ctarank() { uint32_t r; asm volatile("mov.u32 %0, %%cluster_ctarank;" : "=r"(r)); return r; }
__device__ __forceinline__ void cluster_arrive() { asm volatile("barrier.cluster.arrive.release.aligned;" ::: "memory"); }
__device__ __forceinline__ void cluster_wait() { asm volatile("barrier.cluster.wait.acquire.aligned;" ::: "memory"); }
__device__ __forceinline__ void pdl_wait() { asm volatile("griddepcontrol.wait;" ::: "memory"); }
__device__ __forceinline__ void pdl_launch() { asm volatile("griddepcontrol.launch_dependents;" ::: "memory"); }

__device__ __forceinline__ uint32_t pack_bf16(float lo, float hi) {
    uint32_t r;
    asm("cvt.rn.bf16x2.f32 %0, %1, %2;" : "=r"(r) : "f"(hi), "f"(lo));
    return r;
}
__device__ __forceinline__ float ex2(float x) {
    float y;
    asm("ex2.approx.ftz.f32 %0, %1;" : "=f"(y) : "f"(x));
    return y;
}
__device__ __forceinline__ void stmatrix_x4(uint32_t addr, uint32_t r0, uint32_t r1, uint32_t r2, uint32_t r3) {
    asm volatile("stmatrix.sync.aligned.m8n8.x4.shared.b16 [%0], {%1, %2, %3, %4};"
        :: "r"(addr), "r"(r0), "r"(r1), "r"(r2), "r"(r3) : "memory");
}
template<int TA, int TB> __device__ __forceinline__ void wgmma_ss_n128(float (&d)[64], uint64_t descA, uint64_t descB, int scaleD) {
    asm volatile("{\n.reg .pred p;\n"
        "setp.ne.b32 p, %66, 0;\n"
        "wgmma.mma_async.sync.aligned.m64n128k16.f32.bf16.bf16 "
        "{%0,%1,%2,%3,%4,%5,%6,%7,%8,%9,%10,%11,%12,%13,%14,%15,%16,%17,%18,%19,%20,%21,%22,%23,%24,%25,%26,%27,%28,%29,%30,%31,%32,%33,%34,%35,%36,%37,%38,%39,%40,%41,%42,%43,%44,%45,%46,%47,%48,%49,%50,%51,%52,%53,%54,%55,%56,%57,%58,%59,%60,%61,%62,%63}, "
        "%64, %65, p, 1, 1, %67, %68;\n}\n"
        : "+f"(d[0]),"+f"(d[1]),"+f"(d[2]),"+f"(d[3]),"+f"(d[4]),"+f"(d[5]),"+f"(d[6]),"+f"(d[7]),"+f"(d[8]),"+f"(d[9]),"+f"(d[10]),"+f"(d[11]),"+f"(d[12]),"+f"(d[13]),"+f"(d[14]),"+f"(d[15]),"+f"(d[16]),"+f"(d[17]),"+f"(d[18]),"+f"(d[19]),"+f"(d[20]),"+f"(d[21]),"+f"(d[22]),"+f"(d[23]),"+f"(d[24]),"+f"(d[25]),"+f"(d[26]),"+f"(d[27]),"+f"(d[28]),"+f"(d[29]),"+f"(d[30]),"+f"(d[31]),"+f"(d[32]),"+f"(d[33]),"+f"(d[34]),"+f"(d[35]),"+f"(d[36]),"+f"(d[37]),"+f"(d[38]),"+f"(d[39]),"+f"(d[40]),"+f"(d[41]),"+f"(d[42]),"+f"(d[43]),"+f"(d[44]),"+f"(d[45]),"+f"(d[46]),"+f"(d[47]),"+f"(d[48]),"+f"(d[49]),"+f"(d[50]),"+f"(d[51]),"+f"(d[52]),"+f"(d[53]),"+f"(d[54]),"+f"(d[55]),"+f"(d[56]),"+f"(d[57]),"+f"(d[58]),"+f"(d[59]),"+f"(d[60]),"+f"(d[61]),"+f"(d[62]),"+f"(d[63])
        : "l"(descA), "l"(descB), "r"(scaleD), "n"(TA), "n"(TB));
}
template<int TB> __device__ __forceinline__ void wgmma_rs_n128(float (&d)[64], uint32_t a0, uint32_t a1, uint32_t a2, uint32_t a3, uint64_t descB, int scaleD) {
    asm volatile("{\n.reg .pred p;\n"
        "setp.ne.b32 p, %69, 0;\n"
        "wgmma.mma_async.sync.aligned.m64n128k16.f32.bf16.bf16 "
        "{%0,%1,%2,%3,%4,%5,%6,%7,%8,%9,%10,%11,%12,%13,%14,%15,%16,%17,%18,%19,%20,%21,%22,%23,%24,%25,%26,%27,%28,%29,%30,%31,%32,%33,%34,%35,%36,%37,%38,%39,%40,%41,%42,%43,%44,%45,%46,%47,%48,%49,%50,%51,%52,%53,%54,%55,%56,%57,%58,%59,%60,%61,%62,%63}, "
        "{%64,%65,%66,%67}, %68, p, 1, 1, %70;\n}\n"
        : "+f"(d[0]),"+f"(d[1]),"+f"(d[2]),"+f"(d[3]),"+f"(d[4]),"+f"(d[5]),"+f"(d[6]),"+f"(d[7]),"+f"(d[8]),"+f"(d[9]),"+f"(d[10]),"+f"(d[11]),"+f"(d[12]),"+f"(d[13]),"+f"(d[14]),"+f"(d[15]),"+f"(d[16]),"+f"(d[17]),"+f"(d[18]),"+f"(d[19]),"+f"(d[20]),"+f"(d[21]),"+f"(d[22]),"+f"(d[23]),"+f"(d[24]),"+f"(d[25]),"+f"(d[26]),"+f"(d[27]),"+f"(d[28]),"+f"(d[29]),"+f"(d[30]),"+f"(d[31]),"+f"(d[32]),"+f"(d[33]),"+f"(d[34]),"+f"(d[35]),"+f"(d[36]),"+f"(d[37]),"+f"(d[38]),"+f"(d[39]),"+f"(d[40]),"+f"(d[41]),"+f"(d[42]),"+f"(d[43]),"+f"(d[44]),"+f"(d[45]),"+f"(d[46]),"+f"(d[47]),"+f"(d[48]),"+f"(d[49]),"+f"(d[50]),"+f"(d[51]),"+f"(d[52]),"+f"(d[53]),"+f"(d[54]),"+f"(d[55]),"+f"(d[56]),"+f"(d[57]),"+f"(d[58]),"+f"(d[59]),"+f"(d[60]),"+f"(d[61]),"+f"(d[62]),"+f"(d[63])
        : "r"(a0), "r"(a1), "r"(a2), "r"(a3), "l"(descB), "r"(scaleD), "n"(TB));
}
template<int TA, int TB> __device__ __forceinline__ void wgmma_ss_n256(float (&d)[128], uint64_t descA, uint64_t descB, int scaleD) {
    asm volatile("{\n.reg .pred p;\n"
        "setp.ne.b32 p, %130, 0;\n"
        "wgmma.mma_async.sync.aligned.m64n256k16.f32.bf16.bf16 "
        "{%0,%1,%2,%3,%4,%5,%6,%7,%8,%9,%10,%11,%12,%13,%14,%15,%16,%17,%18,%19,%20,%21,%22,%23,%24,%25,%26,%27,%28,%29,%30,%31,%32,%33,%34,%35,%36,%37,%38,%39,%40,%41,%42,%43,%44,%45,%46,%47,%48,%49,%50,%51,%52,%53,%54,%55,%56,%57,%58,%59,%60,%61,%62,%63,%64,%65,%66,%67,%68,%69,%70,%71,%72,%73,%74,%75,%76,%77,%78,%79,%80,%81,%82,%83,%84,%85,%86,%87,%88,%89,%90,%91,%92,%93,%94,%95,%96,%97,%98,%99,%100,%101,%102,%103,%104,%105,%106,%107,%108,%109,%110,%111,%112,%113,%114,%115,%116,%117,%118,%119,%120,%121,%122,%123,%124,%125,%126,%127}, "
        "%128, %129, p, 1, 1, %131, %132;\n}\n"
        : "+f"(d[0]),"+f"(d[1]),"+f"(d[2]),"+f"(d[3]),"+f"(d[4]),"+f"(d[5]),"+f"(d[6]),"+f"(d[7]),"+f"(d[8]),"+f"(d[9]),"+f"(d[10]),"+f"(d[11]),"+f"(d[12]),"+f"(d[13]),"+f"(d[14]),"+f"(d[15]),"+f"(d[16]),"+f"(d[17]),"+f"(d[18]),"+f"(d[19]),"+f"(d[20]),"+f"(d[21]),"+f"(d[22]),"+f"(d[23]),"+f"(d[24]),"+f"(d[25]),"+f"(d[26]),"+f"(d[27]),"+f"(d[28]),"+f"(d[29]),"+f"(d[30]),"+f"(d[31]),"+f"(d[32]),"+f"(d[33]),"+f"(d[34]),"+f"(d[35]),"+f"(d[36]),"+f"(d[37]),"+f"(d[38]),"+f"(d[39]),"+f"(d[40]),"+f"(d[41]),"+f"(d[42]),"+f"(d[43]),"+f"(d[44]),"+f"(d[45]),"+f"(d[46]),"+f"(d[47]),"+f"(d[48]),"+f"(d[49]),"+f"(d[50]),"+f"(d[51]),"+f"(d[52]),"+f"(d[53]),"+f"(d[54]),"+f"(d[55]),"+f"(d[56]),"+f"(d[57]),"+f"(d[58]),"+f"(d[59]),"+f"(d[60]),"+f"(d[61]),"+f"(d[62]),"+f"(d[63]),"+f"(d[64]),"+f"(d[65]),"+f"(d[66]),"+f"(d[67]),"+f"(d[68]),"+f"(d[69]),"+f"(d[70]),"+f"(d[71]),"+f"(d[72]),"+f"(d[73]),"+f"(d[74]),"+f"(d[75]),"+f"(d[76]),"+f"(d[77]),"+f"(d[78]),"+f"(d[79]),"+f"(d[80]),"+f"(d[81]),"+f"(d[82]),"+f"(d[83]),"+f"(d[84]),"+f"(d[85]),"+f"(d[86]),"+f"(d[87]),"+f"(d[88]),"+f"(d[89]),"+f"(d[90]),"+f"(d[91]),"+f"(d[92]),"+f"(d[93]),"+f"(d[94]),"+f"(d[95]),"+f"(d[96]),"+f"(d[97]),"+f"(d[98]),"+f"(d[99]),"+f"(d[100]),"+f"(d[101]),"+f"(d[102]),"+f"(d[103]),"+f"(d[104]),"+f"(d[105]),"+f"(d[106]),"+f"(d[107]),"+f"(d[108]),"+f"(d[109]),"+f"(d[110]),"+f"(d[111]),"+f"(d[112]),"+f"(d[113]),"+f"(d[114]),"+f"(d[115]),"+f"(d[116]),"+f"(d[117]),"+f"(d[118]),"+f"(d[119]),"+f"(d[120]),"+f"(d[121]),"+f"(d[122]),"+f"(d[123]),"+f"(d[124]),"+f"(d[125]),"+f"(d[126]),"+f"(d[127])
        : "l"(descA), "l"(descB), "r"(scaleD), "n"(TA), "n"(TB));
}
template<int TA, int TB> __device__ __forceinline__ void wgmma_ss_n64(float (&d)[32], uint64_t descA, uint64_t descB, int scaleD) {
    asm volatile("{\n.reg .pred p;\n"
        "setp.ne.b32 p, %34, 0;\n"
        "wgmma.mma_async.sync.aligned.m64n64k16.f32.bf16.bf16 "
        "{%0,%1,%2,%3,%4,%5,%6,%7,%8,%9,%10,%11,%12,%13,%14,%15,%16,%17,%18,%19,%20,%21,%22,%23,%24,%25,%26,%27,%28,%29,%30,%31}, "
        "%32, %33, p, 1, 1, %35, %36;\n}\n"
        : "+f"(d[0]),"+f"(d[1]),"+f"(d[2]),"+f"(d[3]),"+f"(d[4]),"+f"(d[5]),"+f"(d[6]),"+f"(d[7]),"+f"(d[8]),"+f"(d[9]),"+f"(d[10]),"+f"(d[11]),"+f"(d[12]),"+f"(d[13]),"+f"(d[14]),"+f"(d[15]),"+f"(d[16]),"+f"(d[17]),"+f"(d[18]),"+f"(d[19]),"+f"(d[20]),"+f"(d[21]),"+f"(d[22]),"+f"(d[23]),"+f"(d[24]),"+f"(d[25]),"+f"(d[26]),"+f"(d[27]),"+f"(d[28]),"+f"(d[29]),"+f"(d[30]),"+f"(d[31])
        : "l"(descA), "l"(descB), "r"(scaleD), "n"(TA), "n"(TB));
}
template<int TA, int TB> __device__ __forceinline__ void wgmma_ss_n96(float (&d)[48], uint64_t descA, uint64_t descB, int scaleD) {
    asm volatile("{\n.reg .pred p;\n"
        "setp.ne.b32 p, %50, 0;\n"
        "wgmma.mma_async.sync.aligned.m64n96k16.f32.bf16.bf16 "
        "{%0,%1,%2,%3,%4,%5,%6,%7,%8,%9,%10,%11,%12,%13,%14,%15,%16,%17,%18,%19,%20,%21,%22,%23,%24,%25,%26,%27,%28,%29,%30,%31,%32,%33,%34,%35,%36,%37,%38,%39,%40,%41,%42,%43,%44,%45,%46,%47}, "
        "%48, %49, p, 1, 1, %51, %52;\n}\n"
        : "+f"(d[0]),"+f"(d[1]),"+f"(d[2]),"+f"(d[3]),"+f"(d[4]),"+f"(d[5]),"+f"(d[6]),"+f"(d[7]),"+f"(d[8]),"+f"(d[9]),"+f"(d[10]),"+f"(d[11]),"+f"(d[12]),"+f"(d[13]),"+f"(d[14]),"+f"(d[15]),"+f"(d[16]),"+f"(d[17]),"+f"(d[18]),"+f"(d[19]),"+f"(d[20]),"+f"(d[21]),"+f"(d[22]),"+f"(d[23]),"+f"(d[24]),"+f"(d[25]),"+f"(d[26]),"+f"(d[27]),"+f"(d[28]),"+f"(d[29]),"+f"(d[30]),"+f"(d[31]),"+f"(d[32]),"+f"(d[33]),"+f"(d[34]),"+f"(d[35]),"+f"(d[36]),"+f"(d[37]),"+f"(d[38]),"+f"(d[39]),"+f"(d[40]),"+f"(d[41]),"+f"(d[42]),"+f"(d[43]),"+f"(d[44]),"+f"(d[45]),"+f"(d[46]),"+f"(d[47])
        : "l"(descA), "l"(descB), "r"(scaleD), "n"(TA), "n"(TB));
}
constexpr int QK_PF = 2;
constexpr int QK_ST = 5;
constexpr int QK_A_BYTES = 128 * 512 * 2;
constexpr int QK_B_BYTES = 64 * 128 * 2;
constexpr int QK_STG = 2 * 64 * 64 * 2;
constexpr int QK_SMEM = QK_A_BYTES + QK_ST * QK_B_BYTES + QK_STG + 1024 + 256
;

__device__ __forceinline__ void unpack8(const uint4& v, float (&f)[8]) {
    const uint32_t u[4] = {v.x, v.y, v.z, v.w};
    #pragma unroll
    for (int i = 0; i < 4; i++) { f[2 * i] = __uint_as_float(u[i] << 16); f[2 * i + 1] = __uint_as_float(u[i] & 0xffff0000u); }
}
__device__ __forceinline__ float warp_sum(float v) {
    #pragma unroll
    for (int o = 16; o > 0; o >>= 1) v += __shfl_xor_sync(0xffffffffu, v, o);
    return v;
}
__device__ __forceinline__ uint4 lds128(uint32_t a) {
    uint4 v; asm volatile("ld.shared.v4.u32 {%0,%1,%2,%3}, [%4];" : "=r"(v.x), "=r"(v.y), "=r"(v.z), "=r"(v.w) : "r"(a)); return v;
}
__device__ __forceinline__ void sts128(uint32_t a, const uint4& v) {
    asm volatile("st.shared.v4.u32 [%0], {%1,%2,%3,%4};" :: "r"(a), "r"(v.x), "r"(v.y), "r"(v.z), "r"(v.w) : "memory");
}
__device__ __forceinline__ uint4 pack8(const float (&f)[8], float sc) {
    uint4 o;
    o.x = pack_bf16(f[0] * sc, f[1] * sc); o.y = pack_bf16(f[2] * sc, f[3] * sc);
    o.z = pack_bf16(f[4] * sc, f[5] * sc); o.w = pack_bf16(f[6] * sc, f[7] * sc);
    return o;
}

__device__ __forceinline__ void ln_rows_inplace(uint32_t sA, int row_base, int lane, uint32_t afull, int nbar, int aph) {
    const int row = row_base + (lane >> 1);
    const uint32_t rowa = sA + row * 128;
    uint32_t off[4];
    #pragma unroll
    for (int i = 0; i < 4; i++) off[i] = rowa + ((((lane & 1) * 4 + i) ^ (row & 7)) << 4);
    float sm0 = 0.f, sm1 = 0.f, sq0 = 0.f, sq1 = 0.f, shift = 0.f;
    #pragma unroll 1
    for (int c = 0; c < 8; c++) {
        if (c < nbar) mbar_wait(afull + 8 * c, aph);
        uint4 v[4];
        #pragma unroll
        for (int i = 0; i < 4; i++) v[i] = lds128(off[i] + c * 16384);
        if (c == 0) shift = __shfl_sync(0xffffffffu, __uint_as_float(v[0].x << 16), lane & ~1);
        #pragma unroll
        for (int i = 0; i < 4; i++) {
            float f[8]; unpack8(v[i], f);
            #pragma unroll
            for (int e = 0; e < 8; e += 2) {
                const float a = f[e] - shift, b = f[e + 1] - shift;
                sm0 += a; sm1 += b; sq0 = fmaf(a, a, sq0); sq1 = fmaf(b, b, sq1);
            }
        }
    }
    float sm = sm0 + sm1, sq = sq0 + sq1;
    sm += __shfl_xor_sync(0xffffffffu, sm, 1); sq += __shfl_xor_sync(0xffffffffu, sq, 1);
    const float dm = sm * (1.f / DM);
    const float var = fmaxf(sq * (1.f / DM) - dm * dm, 0.f);
    const float rs = rsqrtf(var + LN_EPS), nb = -(dm + shift) * rs;
    #pragma unroll 2
    for (int c = 0; c < 8; c++) {
        uint4 v[4];
        #pragma unroll
        for (int i = 0; i < 4; i++) v[i] = lds128(off[i] + c * 16384);
        #pragma unroll
        for (int i = 0; i < 4; i++) {
            float f[8]; unpack8(v[i], f);
            uint4 o;
            o.x = pack_bf16(fmaf(f[0], rs, nb), fmaf(f[1], rs, nb)); o.y = pack_bf16(fmaf(f[2], rs, nb), fmaf(f[3], rs, nb));
            o.z = pack_bf16(fmaf(f[4], rs, nb), fmaf(f[5], rs, nb)); o.w = pack_bf16(fmaf(f[6], rs, nb), fmaf(f[7], rs, nb));
            sts128(off[i] + c * 16384, o);
        }
    }
}

__device__ __forceinline__ int qkv_tile_id(int g, int i) {
    if (g < 2 || (g == 2 && i < 8)) {
        const int idx = i < 8 ? 3 * i + g : 24 + 2 * (i - 8) + g;
        return 31 - idx;
    }
    const int idx = i < 8 ? 5 * i + (g - 3) : 40 + 6 * (i - 8) + (g - 2);
    return 32 * (1 + (idx & 1)) + 31 - (idx >> 1);
}
struct QkvCtx {
    uint32_t sA, sBst, sStg, full, empty, sfull, sempty;
    int s, ph;
    int sph;
    int w, wq, lane;
};

__device__ __forceinline__ void qkv_epi_slice(const float (&acc)[64], int j2, uint32_t stg_row, int lane) {
    const int j = 2 * j2;
    const int cg = (j & 7) + (lane >> 4);
    stmatrix_x4(stg_row + ((cg ^ (lane & 7)) << 4),
                pack_bf16(acc[4 * j], acc[4 * j + 1]), pack_bf16(acc[4 * j + 2], acc[4 * j + 3]),
                pack_bf16(acc[4 * j + 4], acc[4 * j + 5]), pack_bf16(acc[4 * j + 6], acc[4 * j + 7]));
}
__device__ __forceinline__ void qkv_stg_acquire(QkvCtx& c) { mbar_wait(c.sempty + 8 * c.w, c.sph ^ 1); }
__device__ __forceinline__ void qkv_stg_publish(QkvCtx& c) {
    __syncwarp();
    if (c.lane == 0) mbar_arrive(c.sfull + 8 * c.w);
    c.sph ^= 1;
}
__device__ __forceinline__ void qkv_release(const QkvCtx& c, int stage) {
    if (c.wq < 2 && c.lane == 0) mbar_arrive_cta(c.empty + 8 * stage, c.wq);
}

#define PROF_SKIP 0
#define QTS()
template<bool WAIT_A, bool HAS_PREV, int W>
__device__ __forceinline__ void qkv_tile(QkvCtx& c, float (&cur)[64], float (&prev)[64], uint32_t afull, int aph) {
    const uint64_t dA = make_desc(c.sA + c.w * 8192, 16, 1024);
    const int r = (c.lane & 7) + ((c.lane >> 3) & 1) * 8;
    const uint32_t stg_row = c.sStg + c.w * 8192 + (c.wq * 16 + r) * 128;
    #pragma unroll
    for (int kb = 0; kb < 8; kb++) {
        QTS();
        if (WAIT_A) mbar_wait(afull + 8 * kb, aph);
        mbar_wait(c.full + 8 * c.s, c.ph);
        QTS();
        const uint64_t dB = make_desc(c.sBst + c.s * QK_B_BYTES, 8192, 1024);
        wgmma_fence();
        #pragma unroll
        for (int k = 0; k < 4; k++)
            wgmma_ss_n128<0, 1>(cur, desc_add(dA, kb * 16384 + k * 32), desc_add(dB, k * 2048), (kb | k) != 0);
        wgmma_commit();
        const int scur = c.s;
        const int sprev = c.s == 0 ? QK_ST - 1 : c.s - 1;
        if (++c.s == QK_ST) { c.s = 0; c.ph ^= 1; }
        QTS();
        if (kb > 0) { wgmma_wait<1>(); qkv_release(c, sprev); }
        QTS();
        if (HAS_PREV) {
            const int e = kb - 2 * W;
            if (e == 0 || e == 4) qkv_stg_acquire(c);
            if (e == 0 || e == 1 || e == 4 || e == 5) {
                const int j2 = (e >> 2) * 4 + (e & 1) * 2;
                qkv_epi_slice(prev, j2, stg_row, c.lane); qkv_epi_slice(prev, j2 + 1, stg_row, c.lane);
            }
            if (e == 1 || e == 5) qkv_stg_publish(c);
        }
        if (kb == 7) {
            wgmma_wait<0>();
            fence_regs(cur);
            qkv_release(c, scur);
        }
    }
}
__device__ __forceinline__ void qkv_drain(QkvCtx& c, float (&acc)[64], uint32_t aempty) {
    if (c.lane == 0) mbar_arrive(aempty);
    const int r = (c.lane & 7) + ((c.lane >> 3) & 1) * 8;
    const uint32_t stg_row = c.sStg + c.w * 8192 + (c.wq * 16 + r) * 128;
    #pragma unroll
    for (int h = 0; h < 2; h++) {
        qkv_stg_acquire(c);
        #pragma unroll
        for (int j = 0; j < 4; j++) qkv_epi_slice(acc, 4 * h + j, stg_row, c.lane);
        qkv_stg_publish(c);
    }
}

__global__ void __cluster_dims__(2, 1, 1) __launch_bounds__(384, 1)
k_qkv(const __grid_constant__ CUtensorMap mX, const __grid_constant__ CUtensorMap mC,
      const __grid_constant__ CUtensorMap mWq, const __grid_constant__ CUtensorMap mWk,
      const __grid_constant__ CUtensorMap mWv, const __grid_constant__ CUtensorMap mOut,
      const bf16* __restrict__ x, bf16* __restrict__ hacc,
      const bf16* __restrict__ wq, const bf16* __restrict__ wk, const bf16* __restrict__ wv) {
    TL_START(0);
#define TS2()
    TS2();
    extern __shared__ uint8_t smem_raw[];
    const uint32_t sA = (smem_u32(smem_raw) + 1023) & ~1023u;
    const uint32_t sBst = sA + QK_A_BYTES, sStg = sBst + QK_ST * QK_B_BYTES, sB = sStg + QK_STG;
    const uint32_t full = sB, empty = full + 8 * QK_ST, afull = empty + 8 * QK_ST, aempty = afull + 64,
                   sfull = aempty + 8, sempty = sfull + 16;
    const int warp = __shfl_sync(0xffffffffu, threadIdx.x >> 5, 0);
    const int lane = threadIdx.x & 31;
    const uint32_t rank = cluster_ctarank();
    const int cl = blockIdx.x >> 1;
    const int rowblk = (cl >> 3) * 2 + rank;
    const int g = cl & 7;
    const int nseg = (g == 2) ? 2 : 1;
    if (warp == 0 && elect_one()) {
        for (int i = 0; i < QK_ST; i++) { mbar_init(full + 8 * i, 1); mbar_init(empty + 8 * i, 4); }
        for (int i = 0; i < 8; i++) mbar_init(afull + 8 * i, 1);
        mbar_init(aempty, 8);
        for (int i = 0; i < 2; i++) { mbar_init(sfull + 8 * i, 4); mbar_init(sempty + 8 * i, 1); }
        fence_mbar_init();
        fence_proxy_async();
        const CUtensorMap* mA = (g < 3) ? &mX : &mC;
        const int n_early = (g < 3) ? 8 : 2;
        for (int kb = 0; kb < n_early; kb++) {
            mbar_expect_tx(afull + 8 * kb, 16384);
            tma_load_2d(sA + kb * 16384, mA, afull + 8 * kb, kb * 64, rowblk * 128);
        }
    }
    __syncthreads();
    TS2();
    asm volatile("barrier.cluster.arrive.relaxed.aligned;" ::: "memory");
    cluster_wait();
    pdl_launch();
    TS2();

    if (warp < 4) {
        reg_dealloc<40>();
        if (warp == 0) {
            if (elect_one()) {
                int s = 0, ph = 1;
                for (int i = 0; i < 12; i++) {
                    if (g == 2 && i == 8) {
                        mbar_wait(aempty, 0);
                        for (int kb = 0; kb < 8; kb++) {
                            mbar_expect_tx(afull + 8 * kb, 16384);
                            tma_load_2d(sA + kb * 16384, &mC, afull + 8 * kb, kb * 64, rowblk * 128);
                        }
                    }
                    const int n = qkv_tile_id(g, i);
                    const CUtensorMap* mW = n < 32 ? &mWq : (n < 64 ? &mWk : &mWv);
                    const int col = (n & 31) * 128 + rank * 64;
                    for (int kb = 0; kb < 8; kb++) {
                        mbar_wait(empty + 8 * s, ph);
                        mbar_expect_tx(full + 8 * s, QK_B_BYTES);
                        tma_load_2d_mc(sBst + s * QK_B_BYTES + rank * 8192, mW, full + 8 * s, col, kb * 64, (uint16_t)3);
                        if (++s == QK_ST) { s = 0; ph ^= 1; }
                        if (i == 0 && g >= 3 && kb < 6) {
                            mbar_expect_tx(afull + 8 * (kb + 2), 16384);
                            tma_load_2d(sA + (kb + 2) * 16384, &mC, afull + 8 * (kb + 2), (kb + 2) * 64, rowblk * 128);
                        }
                    }
                }
                for (int i = 0; i < QK_ST; i++) { mbar_wait(empty + 8 * s, ph); if (++s == QK_ST) { s = 0; ph ^= 1; } }
            }
        } else if (warp < 3) {
            const int w = warp - 1;
            const bool leader = elect_one();
            for (int i = 0; i < 24; i++) {
                if (leader) {
                    mbar_wait(sfull + 8 * w, i & 1);
                    fence_proxy_async();
                    tma_store_2d(&mOut, sStg + w * 8192, (i & 1) * 64, qkv_tile_id(g, i >> 1) * S_LEN + rowblk * 128 + w * 64);
                    tma_commit();
                }
                __syncwarp();
                const int ip = (i >> 1) + QK_PF + 1;
                if ((i & 1) == 0 && ip < 12) {
                    const int np = qkv_tile_id(g, ip);
                    prefetch_l2((np < 32 ? wq : (np < 64 ? wk : wv)) + (size_t)((cl >> 3) * 64 + w * 32 + lane) * (NH * HD) + (np & 31) * 128 + rank * 64);
                }
                if (leader) {
                    tma_wait_read<0>();
                    mbar_arrive(sempty + 8 * w);
                }
            }
            if (leader) { tma_wait<0>(); TL_END(0); }
        } else {
            mbar_wait(afull + 8 * 7, 0);
            for (int i = 1; i < QK_PF + 1; i++) {
                const int np = qkv_tile_id(g, i);
                const bf16* wp = (np < 32 ? wq : (np < 64 ? wk : wv)) + (size_t)((cl >> 3) * 64 + lane) * (NH * HD) + (np & 31) * 128 + rank * 64;
                prefetch_l2(wp); prefetch_l2(wp + 32 * (NH * HD));
            }
            const uint4* xs = reinterpret_cast<const uint4*>(x + (size_t)blockIdx.x * 16 * DM);
            uint4* hd = reinterpret_cast<uint4*>(hacc + (size_t)blockIdx.x * 16 * DM);
            #pragma unroll 4
            for (int i = lane; i < 16 * DM / 8; i += 32) hd[i] = __ldg(xs + i);
        }
    } else {
        reg_alloc<232>();
        QkvCtx c;
        c.sA = sA; c.sBst = sBst; c.sStg = sStg; c.full = full; c.empty = empty; c.sfull = sfull; c.sempty = sempty;
        c.s = 0; c.ph = 0; c.sph = 0; c.w = (warp >> 2) - 1; c.wq = warp & 3; c.lane = lane;
        float acc0[64], acc1[64];
        for (int seg = 0; seg < nseg; seg++) {
            const int cnt = (nseg == 1) ? 12 : (seg == 0 ? 8 : 4);
            const int aph = seg & 1;
            if (g < 3 && seg == 0) {
                TS2();
                ln_rows_inplace(sA, c.w * 64 + c.wq * 16, lane, afull, 8, aph);
                TS2();
                fence_proxy_async();
                bar_sync(3 + c.w, 128);
                TS2();
            }
            if (c.w == 0) {
                qkv_tile<true, false, 0>(c, acc0, acc1, afull, aph);
                qkv_tile<false, true, 0>(c, acc1, acc0, afull, aph);
                for (int i = 2; i < cnt; i += 2) {
                    qkv_tile<false, true, 0>(c, acc0, acc1, afull, aph);
                    qkv_tile<false, true, 0>(c, acc1, acc0, afull, aph);
                }
            } else {
                qkv_tile<true, false, 1>(c, acc0, acc1, afull, aph);
                qkv_tile<false, true, 1>(c, acc1, acc0, afull, aph);
                for (int i = 2; i < cnt; i += 2) {
                    qkv_tile<false, true, 1>(c, acc0, acc1, afull, aph);
                    qkv_tile<false, true, 1>(c, acc1, acc0, afull, aph);
                }
            }
            qkv_drain(c, acc1, aempty);
        }
        TS2();
    }
}
constexpr int AT_KST = 2, AT_VST = 2;
constexpr int AT_TILE = 128 * 128 * 2;
constexpr int AT_SMEM = (3 + AT_KST + AT_VST) * AT_TILE + 1024 + 256
;
constexpr float AT_SCALE = 0.08838834764831845f * 1.4426950408889634f;
constexpr float AT_BIG = 1073741824.f;
#define AT_PF 0
#define AT_FAST 0
#define AT_PINGPONG 1

struct PrefetchList { const void* ptr[5]; uint32_t bytes[5]; float* colsum; };

__device__ __forceinline__ bool attn_get_tile(int t, int& head, int& qt) {
    int p = blockIdx.x + (t >> 1) * gridDim.x;
    if (p >= NH * 8) return false;
    head = p >> 3;
    int i = p & 7;
    qt = (t & 1) ? i : 15 - i;
    return true;
}

__device__ __forceinline__ void attn_prefetch_kv(const bf16* qkv, int head, int b, int i8, int lane) {
    const int n = min(8, 16 - b);
    const int per = (256 + n - 1) / n;
    const bf16* kp = qkv + ((size_t)(NH + head) * S_LEN + b * 128) * HD;
    const bf16* vp = qkv + ((size_t)(2 * NH + head) * S_LEN + b * 128) * HD;
    for (int l = i8 * per + lane; l < min(256, (i8 + 1) * per); l += 32) { prefetch_l2(kp + l * 64); prefetch_l2(vp + l * 64); }
}
__device__ __forceinline__ void attn_qk(float (&S)[64], uint64_t dq, uint64_t dk) {
    #pragma unroll
    for (int k = 0; k < 8; k++) {
        const uint32_t off = (k >> 2) * 16384 + (k & 3) * 32;
        wgmma_ss_n128<0, 0>(S, desc_add(dq, off), desc_add(dk, off), k > 0);
    }
}
__device__ __forceinline__ void attn_pv(float (&O)[64], uint32_t (&P)[32], uint64_t dv, int acc) {
    #pragma unroll
    for (int k = 0; k < 8; k++)
        wgmma_rs_n128<1>(O, P[4 * k], P[4 * k + 1], P[4 * k + 2], P[4 * k + 3], desc_add(dv, k * 2048), k > 0 ? 1 : acc);
}
__device__ __forceinline__ float quad_max(float v) {
    v = fmaxf(v, __shfl_xor_sync(0xffffffffu, v, 1));
    return fmaxf(v, __shfl_xor_sync(0xffffffffu, v, 2));
}
__device__ __forceinline__ float quad_sum(float v) {
    v += __shfl_xor_sync(0xffffffffu, v, 1);
    return v + __shfl_xor_sync(0xffffffffu, v, 2);
}
__device__ __forceinline__ void attn_rowmax(const float (&S)[64], float& mx0, float& mx1) {
    float a0 = fmaxf(S[0], S[1]), a1 = fmaxf(S[2], S[3]), b0 = fmaxf(S[4], S[5]), b1 = fmaxf(S[6], S[7]);
    #pragma unroll
    for (int j = 2; j < 16; j += 2) {
        a0 = fmaxf(a0, fmaxf(S[4 * j], S[4 * j + 1]));
        a1 = fmaxf(a1, fmaxf(S[4 * j + 2], S[4 * j + 3]));
        b0 = fmaxf(b0, fmaxf(S[4 * j + 4], S[4 * j + 5]));
        b1 = fmaxf(b1, fmaxf(S[4 * j + 6], S[4 * j + 7]));
    }
    mx0 = quad_max(fmaxf(a0, b0));
    mx1 = quad_max(fmaxf(a1, b1));
}
__device__ __forceinline__ void attn_exp(float (&S)[64], float m0, float m1, float& s0, float& s1) {
    const float ms0 = -m0 * AT_SCALE, ms1 = -m1 * AT_SCALE;
    float a0 = 0.f, a1 = 0.f, b0 = 0.f, b1 = 0.f;
    #pragma unroll
    for (int j = 0; j < 16; j++) {
        S[4 * j]     = ex2(fmaf(S[4 * j],     AT_SCALE, ms0));
        S[4 * j + 1] = ex2(fmaf(S[4 * j + 1], AT_SCALE, ms0));
        S[4 * j + 2] = ex2(fmaf(S[4 * j + 2], AT_SCALE, ms1));
        S[4 * j + 3] = ex2(fmaf(S[4 * j + 3], AT_SCALE, ms1));
        a0 += S[4 * j]; b0 += S[4 * j + 1]; a1 += S[4 * j + 2]; b1 += S[4 * j + 3];
    }
    s0 = a0 + b0; s1 = a1 + b1;
}
__device__ __forceinline__ void attn_exp_pack(float (&S)[64], float ms0, float ms1, uint32_t (&P)[32], float& s0, float& s1) {
    float a0 = 0.f, a1 = 0.f, b0 = 0.f, b1 = 0.f;
    #pragma unroll
    for (int j = 0; j < 16; j++) {
        S[4 * j]     = fmaf(S[4 * j],     AT_SCALE, -ms0);
        S[4 * j + 1] = fmaf(S[4 * j + 1], AT_SCALE, -ms0);
        S[4 * j + 2] = fmaf(S[4 * j + 2], AT_SCALE, -ms1);
        S[4 * j + 3] = fmaf(S[4 * j + 3], AT_SCALE, -ms1);
        const float e0 = ex2(S[4 * j]), e1 = ex2(S[4 * j + 1]), e2 = ex2(S[4 * j + 2]), e3 = ex2(S[4 * j + 3]);
        a0 += e0; b0 += e1; a1 += e2; b1 += e3;
        P[2 * j] = pack_bf16(e0, e1); P[2 * j + 1] = pack_bf16(e2, e3);
    }
    s0 = a0 + b0; s1 = a1 + b1;
}
__device__ __forceinline__ void attn_exp_pack_shift(const float (&S)[64], float d0, float d1, uint32_t (&P)[32], float& s0, float& s1) {
    float a0 = 0.f, a1 = 0.f, b0 = 0.f, b1 = 0.f;
    #pragma unroll
    for (int j = 0; j < 16; j++) {
        const float e0 = ex2(S[4 * j] - d0), e1 = ex2(S[4 * j + 1] - d0), e2 = ex2(S[4 * j + 2] - d1), e3 = ex2(S[4 * j + 3] - d1);
        a0 += e0; b0 += e1; a1 += e2; b1 += e3;
        P[2 * j] = pack_bf16(e0, e1); P[2 * j + 1] = pack_bf16(e2, e3);
    }
    s0 = a0 + b0; s1 = a1 + b1;
}
__device__ __forceinline__ void attn_cvt(const float (&S)[64], uint32_t (&P)[32]) {
    #pragma unroll
    for (int i = 0; i < 32; i++) P[i] = pack_bf16(S[2 * i], S[2 * i + 1]);
}

__global__ void __launch_bounds__(384, 1)
k_attn(const __grid_constant__ CUtensorMap mQKV, const __grid_constant__ CUtensorMap mCtx, const PrefetchList pf, const bf16* __restrict__ qkv) {
    TL_START(1);
#define TS6()
    TS6();
    extern __shared__ uint8_t smem_raw[];
    const uint32_t sQ = (smem_u32(smem_raw) + 1023) & ~1023u;
    const uint32_t sK = sQ + 2 * AT_TILE, sV = sK + AT_KST * AT_TILE, sO = sV + AT_VST * AT_TILE, sB = sO + AT_TILE;
    const uint32_t qfull = sB, qempty = sB + 16, kfull = sB + 32, kempty = kfull + 8 * AT_KST,
                   vfull = kempty + 8 * AT_KST, vempty = vfull + 8 * AT_VST, ofull = vempty + 8 * AT_VST, oempty = ofull + 16;
    const int warp = __shfl_sync(0xffffffffu, threadIdx.x >> 5, 0);
    const int lane = threadIdx.x & 31;
    if (threadIdx.x == 0) {
        for (int i = 0; i < 2; i++) { mbar_init(qfull + 8 * i, 1); mbar_init(qempty + 8 * i, 2); mbar_init(ofull + 8 * i, 4); mbar_init(oempty + 8 * i, 1); }
        for (int i = 0; i < AT_KST; i++) { mbar_init(kfull + 8 * i, 1); mbar_init(kempty + 8 * i, 2); }
        for (int i = 0; i < AT_VST; i++) { mbar_init(vfull + 8 * i, 1); mbar_init(vempty + 8 * i, 2); }
        fence_mbar_init();
        prefetch_tmap(&mQKV); prefetch_tmap(&mCtx);
    }
    __syncthreads();
    TS6();
    pdl_launch();
    pdl_wait();
    TS6();
    if (threadIdx.x == 0) { TL_MARK(1); }

    if (warp < 4) {
        reg_dealloc<40>();
        if (warp == 0) {
          if (elect_one()) {
            int ks = 0, kph = 1, vs = 0, vph = 1;
            int head, qt;
            bool have = attn_get_tile(0, head, qt);
            if (have) {
                mbar_expect_tx(qfull, AT_TILE);
                tma_load_3d(sQ, &mQKV, qfull, 0, head * S_LEN + qt * 128, 0);
            }
            for (int t = 0; have; t++) {
                const int krow = (NH + head) * S_LEN, vrow = (2 * NH + head) * S_LEN;
                for (int j = 0; j <= qt + 1; j++) {
                    if (j <= qt) {
                        mbar_wait(kempty + 8 * ks, kph);
                        mbar_expect_tx(kfull + 8 * ks, AT_TILE);
                        tma_load_3d(sK + ks * AT_TILE, &mQKV, kfull + 8 * ks, 0, krow + j * 128, 0);
                        if (++ks == AT_KST) { ks = 0; kph ^= 1; }
                    }
                    if (j > 0) {
                        mbar_wait(vempty + 8 * vs, vph);
                        mbar_expect_tx(vfull + 8 * vs, AT_TILE);
                        tma_load_3d(sV + vs * AT_TILE, &mQKV, vfull + 8 * vs, 0, vrow + (j - 1) * 128, 0);
                        if (++vs == AT_VST) { vs = 0; vph ^= 1; }
                    }
                }
                have = attn_get_tile(t + 1, head, qt);
                if (have) {
                    const int b = (t + 1) & 1, u = (t + 1) >> 1;
                    mbar_wait(qempty + 8 * b, (u & 1) ^ 1);
                    mbar_expect_tx(qfull + 8 * b, AT_TILE);
                    tma_load_3d(sQ + b * AT_TILE, &mQKV, qfull + 8 * b, 0, head * S_LEN + qt * 128, 0);
                }
            }
          }
        } else if (warp == 1 || warp == 2) {
            const int w = warp - 1;
            for (int c0 = (blockIdx.x * 2 + w) * 8; c0 < DM + FF; c0 += gridDim.x * 16) {
                const bool first = c0 < DM;
                const bf16* wp = first ? static_cast<const bf16*>(pf.ptr[1]) + c0 : static_cast<const bf16*>(pf.ptr[3]) + (c0 - DM);
                const int ld = first ? DM : FF;
                float a[8] = {0.f, 0.f, 0.f, 0.f, 0.f, 0.f, 0.f, 0.f};
                #pragma unroll 2
                for (int r = lane; r < DM; r += 32) {
                    float f[8]; unpack8(__ldg(reinterpret_cast<const uint4*>(wp + (size_t)r * ld)), f);
                    #pragma unroll
                    for (int e = 0; e < 8; e++) a[e] += f[e];
                }
                #pragma unroll
                for (int e = 0; e < 8; e++) a[e] = warp_sum(a[e]);
                if (lane == 0) {
                    *reinterpret_cast<float4*>(pf.colsum + c0) = make_float4(a[0], a[1], a[2], a[3]);
                    *reinterpret_cast<float4*>(pf.colsum + c0 + 4) = make_float4(a[4], a[5], a[6], a[7]);
                }
            }
            const bool leader = elect_one();
            int head, qt;
            for (int t = 0; attn_get_tile(t, head, qt); t++) {
                if (leader) {
                    mbar_wait(ofull + 8 * w, t & 1);
                    fence_proxy_async();
                    const uint32_t src = sO + w * 16384;
                    tma_store_2d(&mCtx, src, head * 128, qt * 128 + w * 64);
                    tma_store_2d(&mCtx, src + 8192, head * 128 + 64, qt * 128 + w * 64);
                    tma_commit();
                    tma_wait_read<0>();
                    mbar_arrive(oempty + 8 * w);
                }
                __syncwarp();
                int h2, q2;
                if (t == (attn_get_tile(2, h2, q2) ? 1 : 0)) {
                    #pragma unroll 1
                    for (int k = 0; k < 5; k++) {
                        const char* base = reinterpret_cast<const char*>(pf.ptr[k]);
                        for (uint32_t o = ((blockIdx.x * 2 + w) * 32 + lane) * 128u; o < pf.bytes[k]; o += gridDim.x * 64 * 128u) prefetch_l2(base + o);
                    }
                }
            }
            if (leader) { tma_wait<0>(); TL_END(1); }
        } else if (warp == 3) {
            int ks = 0, kph = 0, vs = 0, vph = 0;
            int head, qt;
            bool have = attn_get_tile(0, head, qt);
            for (int t = 0; have; t++) {
                int nh, nq;
                const bool nxt = attn_get_tile(t + 1, nh, nq);
                const int j0 = (t == 0) ? 0 : 1;
                for (int j = j0; j <= qt + 1; j++) {
                    const bool last = j == qt + 1;
                    if (j == 0) mbar_wait(qfull, 0);
                    if (last && nxt) mbar_wait(qfull + 8 * ((t + 1) & 1), ((t + 1) >> 1) & 1);
                    if (!last || nxt) { mbar_wait(kfull + 8 * ks, kph); if (++ks == AT_KST) { ks = 0; kph ^= 1; } }
                    if (j > 0) { mbar_wait(vfull + 8 * vs, vph); if (++vs == AT_VST) { vs = 0; vph ^= 1; } }
                    bar_sync(1, 288);
                    bar_sync(2, 288);
                }
                have = nxt; qt = nq; head = nh;
            }
        }
    } else {
        reg_alloc<232>();
        const int w = (warp >> 2) - 1;
        const int wq = warp & 3;
        const int row0 = w * 64 + wq * 16 + (lane >> 2);
        const int qc = (lane & 3) * 2;
        if (w == 1) bar_arrive(1, 288);
#define ATS()
        float O[64], S[64];
        uint32_t P0[32], P1[32];
        int ks = 0, vs = 0;
        int head, qt;
        float m0 = 0.f, m1 = 0.f, l0 = 0.f, l1 = 0.f;
        const int thr0 = row0 - qc;

        auto mask_diag = [&]() {
            int thr = thr0;
            asm volatile("" : "+r"(thr));
            #pragma unroll
            for (int j = 0; j < 16; j++) {
                if (8 * j > thr) S[4 * j] = -INFINITY;
                if (8 * j + 1 > thr) S[4 * j + 1] = -INFINITY;
                if (8 * j - 8 > thr) S[4 * j + 2] = -INFINITY;
                if (8 * j - 7 > thr) S[4 * j + 3] = -INFINITY;
            }
        };
        auto epilogue = [&](int t, float i0, float i1) {
            const int r = (lane & 7) + ((lane >> 3) & 1) * 8;
            const uint32_t rowaddr = sO + w * 16384 + (wq * 16 + r) * 128;
            mbar_wait(oempty + 8 * w, (t & 1) ^ 1);
            #pragma unroll
            for (int j = 0; j < 16; j += 2) {
                const int cg = j + (lane >> 4);
                const uint32_t a = rowaddr + (cg >> 3) * 8192 + (((cg & 7) ^ (lane & 7)) << 4);
                stmatrix_x4(a, pack_bf16(O[4 * j] * i0, O[4 * j + 1] * i0), pack_bf16(O[4 * j + 2] * i1, O[4 * j + 3] * i1),
                               pack_bf16(O[4 * j + 4] * i0, O[4 * j + 5] * i0), pack_bf16(O[4 * j + 6] * i1, O[4 * j + 7] * i1));
            }
            __syncwarp();
            if (lane == 0) mbar_arrive(ofull + 8 * w);
        };
        const uint32_t sig = (wq == 0 && lane == 0);
        int t = 0, j = 1;
        int nhead = 0, nqt = 0;
        bool have_next = false;
        auto step = [&](uint32_t (&Pin)[32], uint32_t (&Pout)[32]) {
            const bool trans = j > qt;
            const int qb = (t + (trans ? 1 : 0)) & 1;
            ATS();
            bar_sync(1 + w, 288);
            ATS();
            wgmma_fence();
            attn_qk(S, make_desc(sQ + qb * AT_TILE + w * 8192, 16, 1024), make_desc(sK + ks * AT_TILE, 16, 1024));
            wgmma_commit();
            attn_pv(O, Pin, make_desc(sV + vs * AT_TILE, 16384, 1024), j != 1);
            wgmma_commit();
            bar_arrive(1 + (w ^ 1), 288);
            ATS();
            wgmma_wait<1>();
            fence_regs(S);
            ATS();
            const bool diag = trans ? (nqt == 0) : (j == qt);
            mbar_arrive_if(kempty + 8 * ks, sig);
            mbar_arrive_if(qempty + 8 * qb, sig && diag);
            ks ^= 1;
            if (__builtin_expect(diag, 0)) mask_diag();
            float lp0 = l0, lp1 = l1;
            if (__builtin_expect(trans, 0)) {
                attn_rowmax(S, m0, m1);
                m0 *= AT_SCALE; m1 *= AT_SCALE;
                l0 = 0.f; l1 = 0.f;
            }
            ATS();
            float s0, s1;
            attn_exp_pack(S, m0, m1, Pout, s0, s1);
            const bool bad = __any_sync(0xffffffffu, !(s0 <= AT_BIG && s1 <= AT_BIG));
            ATS();
            if (__builtin_expect(bad, 0)) {
                asm volatile("wgmma.wait_group.sync.aligned 0; // fallback" ::: "memory");
                fence_regs(O);
                float d0, d1;
                attn_rowmax(S, d0, d1);
                d0 = fmaxf(d0, 0.f); d1 = fmaxf(d1, 0.f);
                m0 += d0; m1 += d1;
                if (!trans) {
                    const float sc0 = ex2(-d0), sc1 = ex2(-d1);
                    l0 *= sc0; l1 *= sc1;
                    #pragma unroll
                    for (int i = 0; i < 16; i++) {
                        O[4 * i] *= sc0; O[4 * i + 1] *= sc0; O[4 * i + 2] *= sc1; O[4 * i + 3] *= sc1;
                    }
                }
                attn_exp_pack_shift(S, d0, d1, Pout, s0, s1);
            } else {
                asm volatile("wgmma.wait_group.sync.aligned 0; // common" ::: "memory");
            }
            fence_regs(O); fence_regs(Pin);
            mbar_arrive_if(vempty + 8 * vs, sig);
            vs ^= 1;
            l0 += s0; l1 += s1;
            if (__builtin_expect(trans, 0)) {
                epilogue(t, __fdividef(1.f, quad_sum(lp0)), __fdividef(1.f, quad_sum(lp1)));
                t++; head = nhead; qt = nqt; j = 1;
                have_next = attn_get_tile(t + 1, nhead, nqt);
            } else j++;
            ATS();
        };

        auto fast = [&](uint32_t (&Pin)[32], uint32_t (&Pout)[32]) {
            ATS();
            bar_sync(1 + w, 288);
            ATS();
            wgmma_fence();
            attn_qk(S, make_desc(sQ + (t & 1) * AT_TILE + w * 8192, 16, 1024), make_desc(sK + ks * AT_TILE, 16, 1024));
            wgmma_commit();
            attn_pv(O, Pin, make_desc(sV + vs * AT_TILE, 16384, 1024), j != 1);
            wgmma_commit();
            bar_arrive(1 + (w ^ 1), 288);
            ATS();
            wgmma_wait<1>();
            fence_regs(S);
            ATS();
            mbar_arrive_if(kempty + 8 * ks, sig);
            ks ^= 1;
            ATS();
            float s0, s1;
            attn_exp_pack(S, m0, m1, Pout, s0, s1);
            const bool bad = __any_sync(0xffffffffu, !(s0 <= AT_BIG && s1 <= AT_BIG));
            ATS();
            if (__builtin_expect(bad, 0)) {
                asm volatile("wgmma.wait_group.sync.aligned 0; // fix" ::: "memory");
                fence_regs(O);
                float d0, d1;
                attn_rowmax(S, d0, d1);
                d0 = fmaxf(d0, 0.f); d1 = fmaxf(d1, 0.f);
                m0 += d0; m1 += d1;
                const float sc0 = ex2(-d0), sc1 = ex2(-d1);
                l0 *= sc0; l1 *= sc1;
                #pragma unroll
                for (int i = 0; i < 16; i++) {
                    O[4 * i] *= sc0; O[4 * i + 1] *= sc0; O[4 * i + 2] *= sc1; O[4 * i + 3] *= sc1;
                }
                attn_exp_pack_shift(S, d0, d1, Pout, s0, s1);
            } else {
                asm volatile("wgmma.wait_group.sync.aligned 0; // fast" ::: "memory");
            }
            fence_regs(O); fence_regs(Pin);
            mbar_arrive_if(vempty + 8 * vs, sig);
            vs ^= 1;
            l0 += s0; l1 += s1;
            j++;
            ATS();
        };
        auto final_pv = [&](uint32_t (&Pin)[32]) {
            bar_sync(1 + w, 288);
            wgmma_fence();
            attn_pv(O, Pin, make_desc(sV + vs * AT_TILE, 16384, 1024), j != 1);
            wgmma_commit();
            bar_arrive(1 + (w ^ 1), 288);
            const float i0 = __fdividef(1.f, quad_sum(l0)), i1 = __fdividef(1.f, quad_sum(l1));
            wgmma_wait<0>();
            fence_regs(O); fence_regs(Pin);
            epilogue(t, i0, i1);
        };

        if (attn_get_tile(0, head, qt)) {
            have_next = attn_get_tile(1, nhead, nqt);
            TS6();
            bar_sync(1 + w, 288);
            TS6();
            wgmma_fence();
            attn_qk(S, make_desc(sQ + w * 8192, 16, 1024), make_desc(sK + ks * AT_TILE, 16, 1024));
            wgmma_commit();
            bar_arrive(1 + (w ^ 1), 288);
            wgmma_wait<0>();
            fence_regs(S);
            mbar_arrive_if(kempty + 8 * ks, sig);
            mbar_arrive_if(qempty, sig && qt == 0);
            ks ^= 1;
            TS6();
            if (qt == 0) mask_diag();
            attn_rowmax(S, m0, m1);
            m0 *= AT_SCALE; m1 *= AT_SCALE;
            attn_exp_pack(S, m0, m1, P0, l0, l1);
            TS6();
            while (true) {
                if (j > qt && !have_next) { final_pv(P0); break; }
                step(P0, P1);
                if (j > qt && !have_next) { final_pv(P1); break; }
                step(P1, P0);
            }
        }
    }
}
__device__ __forceinline__ float gelu_tanh(float x) {
    const float u = x * fmaf(x * x, 0.044715f * 0.7978845608028654f, 0.7978845608028654f);
    float t;
    asm("tanh.approx.f32 %0, %1;" : "=f"(t) : "f"(u));
    const float hx = 0.5f * x;
    return fmaf(hx, t, hx);
}
__device__ __forceinline__ float gelu_half(float h) {
    const float u = h * fmaf(h * h, 8.f * 0.044715f * 0.7978845608028654f, 2.f * 0.7978845608028654f);
    float t;
    asm("tanh.approx.f32 %0, %1;" : "=f"(t) : "f"(u));
    return fmaf(h, t, h);
}
__device__ __forceinline__ float bf_lo(uint32_t u) { return __uint_as_float(u << 16); }
__device__ __forceinline__ float bf_hi(uint32_t u) { return __uint_as_float(u & 0xffff0000u); }
__device__ __forceinline__ void cluster_sync_relaxed() {
    asm volatile("barrier.cluster.arrive.relaxed.aligned;" ::: "memory");
    cluster_wait();
}

constexpr int GO_ST = 4;
constexpr int GO_STAGE = 16384 + 32768;
constexpr int GO_SMEM = GO_ST * GO_STAGE + 32768 + 1024 + 256;

__global__ void __cluster_dims__(2, 1, 1) __launch_bounds__(384, 1)
k_oproj(const __grid_constant__ CUtensorMap mCtx, const __grid_constant__ CUtensorMap mWo, const __grid_constant__ CUtensorMap mH) {
    TL_START(2);
    GTS_DECL
    GTS();
    extern __shared__ uint8_t smem_raw[];
    const uint32_t s0 = (smem_u32(smem_raw) + 1023) & ~1023u;
    const uint32_t sStg = s0 + GO_ST * GO_STAGE, full = sStg + 32768, empty = full + 8 * GO_ST;
    const int warp = __shfl_sync(0xffffffffu, threadIdx.x >> 5, 0);
    const int lane = threadIdx.x & 31;
    const uint32_t rank = cluster_ctarank();
    const int cl = blockIdx.x >> 1;
    const int rowblk = (cl >> 3) * 2 + rank, nh = cl & 1, ks = (cl >> 1) & 3;
    if (warp == 0 && elect_one()) {
        for (int i = 0; i < GO_ST; i++) { mbar_init(full + 8 * i, 1); mbar_init(empty + 8 * i, 4); }
        fence_mbar_init();
        fence_proxy_async();
        prefetch_tmap(&mCtx); prefetch_tmap(&mWo); prefetch_tmap(&mH);
    }
    __syncthreads();
    cluster_sync_relaxed();
    pdl_launch();
    if (warp < 4) {
        reg_dealloc<40>();
        if (warp == 0 && elect_one()) {
            for (int kb = 0; kb < GO_ST; kb++) {
                mbar_expect_tx(full + 8 * kb, GO_STAGE);
                tma_load_3d_mc(s0 + kb * GO_STAGE + 16384 + rank * 16384, &mWo, full + 8 * kb, 0, ks * 1024 + kb * 64, nh * 4 + rank * 2, (uint16_t)3);
            }
            pdl_wait();
            if (true) { TL_MARK(2); }
            int s = 0, ph = 1;
            for (int kb = 0; kb < 16; kb++) {
                const int k0 = ks * 1024 + kb * 64;
                const uint32_t st = s0 + s * GO_STAGE;
                if (kb >= GO_ST) {
                    mbar_wait(empty + 8 * s, ph);
                    mbar_expect_tx(full + 8 * s, GO_STAGE);
                    tma_load_3d_mc(st + 16384 + rank * 16384, &mWo, full + 8 * s, 0, k0, nh * 4 + rank * 2, (uint16_t)3);
                }
                tma_load_2d(st, &mCtx, full + 8 * s, k0, rowblk * 128);
                if (++s == GO_ST) { s = 0; ph ^= 1; }
            }
            for (int i = 0; i < GO_ST; i++) { mbar_wait(empty + 8 * s, ph); if (++s == GO_ST) { s = 0; ph ^= 1; } }
        }
    } else {
        reg_alloc<232>();
        const int w = (warp >> 2) - 1, wq = warp & 3;
        float accL[64], accH[64];
        int s = 0, ph = 0;
        for (int kb = 0; kb < 16 - GO_ST; kb++) {
            mbar_wait(full + 8 * s, ph);
            if (kb == 0 || kb == 8) GTS();
            const uint32_t st = s0 + s * GO_STAGE;
            const uint64_t dA = make_desc(st + w * 8192, 16, 1024), dB = make_desc(st + 16384, 8192, 1024);
            wgmma_fence();
            #pragma unroll
            for (int k = 0; k < 4; k++) {
                wgmma_ss_n128<0, 1>(accL, desc_add(dA, k * 32), desc_add(dB, k * 2048), (kb | k) != 0);
                wgmma_ss_n128<0, 1>(accH, desc_add(dA, k * 32), desc_add(dB, 16384 + k * 2048), (kb | k) != 0);
            }
            wgmma_commit();
            wgmma_wait<1>();
            if (kb > 0) { const int sp = s == 0 ? GO_ST - 1 : s - 1; if (wq < 2 && lane == 0) mbar_arrive_cta(empty + 8 * sp, wq); }
            if (++s == GO_ST) { s = 0; ph ^= 1; }
        }
        {
            int s2 = s, ph2 = ph;
            #pragma unroll
            for (int i = 0; i < GO_ST; i++) {
                mbar_wait(full + 8 * s2, ph2);
                const uint32_t st = s0 + s2 * GO_STAGE;
                const uint64_t dA = make_desc(st + w * 8192, 16, 1024), dB = make_desc(st + 16384, 8192, 1024);
                wgmma_fence();
                #pragma unroll
                for (int k = 0; k < 4; k++) wgmma_ss_n128<0, 1>(accL, desc_add(dA, k * 32), desc_add(dB, k * 2048), 1);
                if (i == 0) {
                    wgmma_commit();
                    wgmma_wait<1>();
                    const int sp = s == 0 ? GO_ST - 1 : s - 1;
                    if (wq < 2 && lane == 0) mbar_arrive_cta(empty + 8 * sp, wq);
                }
                if (++s2 == GO_ST) { s2 = 0; ph2 ^= 1; }
            }
            wgmma_commit();
            s2 = s;
            #pragma unroll
            for (int i = 0; i < GO_ST; i++) {
                const uint32_t st = s0 + s2 * GO_STAGE;
                const uint64_t dA = make_desc(st + w * 8192, 16, 1024), dB = make_desc(st + 16384, 8192, 1024);
                #pragma unroll
                for (int k = 0; k < 4; k++) wgmma_ss_n128<0, 1>(accH, desc_add(dA, k * 32), desc_add(dB, 16384 + k * 2048), 1);
                if (++s2 == GO_ST) s2 = 0;
            }
            wgmma_commit();
        }
        const int r = (lane & 7) + ((lane >> 3) & 1) * 8;
        auto epi = [&](const float (&a)[64], uint32_t stg, int col0) {
            const uint32_t rowa = stg + (wq * 16 + r) * 128;
            #pragma unroll
            for (int j = 0; j < 16; j += 2) {
                const int cg = j + (lane >> 4);
                stmatrix_x4(rowa + (cg >> 3) * 8192 + (((cg & 7) ^ (lane & 7)) << 4),
                    pack_bf16(a[4 * j], a[4 * j + 1]), pack_bf16(a[4 * j + 2], a[4 * j + 3]),
                    pack_bf16(a[4 * j + 4], a[4 * j + 5]), pack_bf16(a[4 * j + 6], a[4 * j + 7]));
            }
            bar_sync(3 + w, 128);
            if (wq == 0 && elect_one()) {
                fence_proxy_async();
                tma_red_add_2d(&mH, stg + (ks & 1) * 8192, col0 + (ks & 1) * 64, rowblk * 128 + w * 64);
                tma_red_add_2d(&mH, stg + ((ks & 1) ^ 1) * 8192, col0 + ((ks & 1) ^ 1) * 64, rowblk * 128 + w * 64);
                tma_commit();
            }
        };
        wgmma_wait<1>();
        fence_regs(accL);
        GTS();
        epi(accL, sStg + w * 16384, nh * 256);
        wgmma_wait<0>();
        fence_regs(accH);
        GTS();
        if (wq < 2 && lane == 0) {
            for (int i = 0; i < GO_ST; i++) mbar_arrive_cta(empty + 8 * i, wq);
        }
        bar_sync(1, 256);
        epi(accH, s0 + w * 16384, nh * 256 + 128);
        GTS();
        if (wq == 0 && elect_one()) { tma_wait<0>(); GTS(); TL_END(2); }
    }
}

constexpr int G1_SMEM = 65536 + 8 * 16384 + 16384 + 1024 + 64 + 512 + 64;

__global__ void __launch_bounds__(384, 1)
k_g1(const __grid_constant__ CUtensorMap mH, const __grid_constant__ CUtensorMap mW1, const __grid_constant__ CUtensorMap mT1,
     float2* __restrict__ stats, const float* __restrict__ cs1, float2* __restrict__ x1stat) {
    TL_START(3);
    GTS_DECL
    GTS();
    extern __shared__ uint8_t smem_raw[];
    const uint32_t sA = (smem_u32(smem_raw) + 1023) & ~1023u;
    const uint32_t sBm = sA + 65536, sStg = sBm + 8 * 16384, full = sStg + 16384, sStat = full + 64;
    const int warp = __shfl_sync(0xffffffffu, threadIdx.x >> 5, 0);
    const int lane = threadIdx.x & 31;
    const int rb = blockIdx.x >> 2, nq = blockIdx.x & 3;
    if (warp == 0 && elect_one()) {
        for (int i = 0; i < 8; i++) mbar_init(full + 8 * i, 1);
        fence_mbar_init();
        fence_proxy_async();
        for (int kb = 0; kb < 8; kb++) {
            mbar_expect_tx(full + 8 * kb, 16384 + 8192);
            tma_load_3d(sBm + kb * 16384, &mW1, full + 8 * kb, 0, kb * 64, nq * 2);
        }
        prefetch_tmap(&mH); prefetch_tmap(&mT1);
    }
    __syncthreads();
    pdl_launch();
    if (warp < 4) {
        if (warp == 0 && elect_one()) {
            pdl_wait();
            if (true) { TL_MARK(3); }
            for (int kb = 0; kb < 8; kb++) tma_load_2d(sA + kb * 8192, &mH, full + 8 * kb, kb * 64, rb * 64);
        }
    } else {
        const int w = (warp >> 2) - 1, wq = warp & 3;
        pdl_wait();
        float cs[16];
        #pragma unroll
        for (int j = 0; j < 8; j++) {
            const float2 t = __ldcg(reinterpret_cast<const float2*>(cs1 + nq * 128 + w * 64 + j * 8 + (lane & 3) * 2));
            cs[2 * j] = t.x; cs[2 * j + 1] = t.y;
        }
        const int srow = (warp - 4) * 8 + (lane >> 2);
        uint32_t soff[2];
        #pragma unroll
        for (int i = 0; i < 2; i++) soff[i] = sA + srow * 128 + ((((lane & 3) * 2 + i) ^ (srow & 7)) << 4);
        float sm0 = 0.f, sm1 = 0.f, sq0 = 0.f, sq1 = 0.f, shift = 0.f;
        float acc[32];
        const uint64_t dA = make_desc(sA, 16, 1024);
        #pragma unroll
        for (int kb = 0; kb < 8; kb++) {
            mbar_wait(full + 8 * kb, 0);
            if (kb == 0) GTS();
            wgmma_fence();
            const uint64_t dB = make_desc(sBm + kb * 16384 + w * 8192, 8192, 1024);
            #pragma unroll
            for (int k = 0; k < 4; k++) wgmma_ss_n64<0, 1>(acc, desc_add(dA, kb * 8192 + k * 32), desc_add(dB, k * 2048), (kb | k) != 0);
            wgmma_commit();
            const uint4 v0 = lds128(soff[0] + kb * 8192), v1 = lds128(soff[1] + kb * 8192);
            if (kb == 0) shift = __shfl_sync(0xffffffffu, __uint_as_float(v0.x << 16), lane & ~3);
            float f0[8], f1[8]; unpack8(v0, f0); unpack8(v1, f1);
            #pragma unroll
            for (int e = 0; e < 8; e++) {
                const float a = f0[e] - shift, b = f1[e] - shift;
                sm0 += a; sm1 += b; sq0 = fmaf(a, a, sq0); sq1 = fmaf(b, b, sq1);
            }
        }
        {
            float sm = sm0 + sm1, sq = sq0 + sq1;
            sm += __shfl_xor_sync(0xffffffffu, sm, 1); sq += __shfl_xor_sync(0xffffffffu, sq, 1);
            sm += __shfl_xor_sync(0xffffffffu, sm, 2); sq += __shfl_xor_sync(0xffffffffu, sq, 2);
            const float dm = sm * (1.f / DM);
            const float var = fmaxf(sq * (1.f / DM) - dm * dm, 0.f), mean = dm + shift;
            const float rstd = rsqrtf(var + LN_EPS);
            const float sc = 0.5f * rstd * rsqrtf(var * rstd * rstd + LN_EPS);
            if ((lane & 3) == 0) {
                asm volatile("st.shared.v2.f32 [%0], {%1, %2};" :: "r"(sStat + srow * 8), "f"(mean), "f"(sc) : "memory");
                if (nq == 0) { stats[rb * 64 + srow] = make_float2(mean, rstd); x1stat[rb * 64 + srow] = make_float2(0.f, 0.f); }
            }
        }
        bar_sync(1, 256);
        float mean0, sc0, mean1, sc1;
        asm volatile("ld.shared.v2.f32 {%0, %1}, [%2];" : "=f"(mean0), "=f"(sc0) : "r"(sStat + (wq * 16 + (lane >> 2)) * 8));
        asm volatile("ld.shared.v2.f32 {%0, %1}, [%2];" : "=f"(mean1), "=f"(sc1) : "r"(sStat + (wq * 16 + (lane >> 2) + 8) * 8));
        wgmma_wait<0>();
        fence_regs(acc);
        GTS();
        #pragma unroll
        for (int j = 0; j < 8; j++) {
            acc[4 * j]     = gelu_half(fmaf(-mean0, cs[2 * j],     acc[4 * j])     * sc0);
            acc[4 * j + 1] = gelu_half(fmaf(-mean0, cs[2 * j + 1], acc[4 * j + 1]) * sc0);
            acc[4 * j + 2] = gelu_half(fmaf(-mean1, cs[2 * j],     acc[4 * j + 2]) * sc1);
            acc[4 * j + 3] = gelu_half(fmaf(-mean1, cs[2 * j + 1], acc[4 * j + 3]) * sc1);
        }
        const int r = (lane & 7) + ((lane >> 3) & 1) * 8;
        const uint32_t rowa = sStg + w * 8192 + (wq * 16 + r) * 128;
        #pragma unroll
        for (int j = 0; j < 8; j += 2) {
            const int cg = j + (lane >> 4);
            stmatrix_x4(rowa + ((cg ^ (lane & 7)) << 4),
                pack_bf16(acc[4 * j], acc[4 * j + 1]), pack_bf16(acc[4 * j + 2], acc[4 * j + 3]),
                pack_bf16(acc[4 * j + 4], acc[4 * j + 5]), pack_bf16(acc[4 * j + 6], acc[4 * j + 7]));
        }
        bar_sync(3 + w, 128);
        if (wq == 0 && elect_one()) {
            fence_proxy_async();
            tma_store_2d(&mT1, sStg + w * 8192, nq * 128 + w * 64, rb * 64);
            tma_commit();
            GTS();
            tma_wait<0>();
            GTS();
            TL_END(3);
        }
    }
}

constexpr int GS_ST = 8;
constexpr int GS_STAGE = 16384 + 8192;
constexpr int GS_SMEM = GS_ST * GS_STAGE + 16384 + 1024 + 256;

template<int MODE>
__global__ void __cluster_dims__(2, 1, 1) __launch_bounds__(384, 1)
k_gs(const __grid_constant__ CUtensorMap mA, const __grid_constant__ CUtensorMap mW, const __grid_constant__ CUtensorMap mOut,
     const bf16* __restrict__ h, const float2* __restrict__ stats, const bf16* __restrict__ x1, float2* __restrict__ x1stat) {
    TL_START((MODE == 0 ? 4 : 6));
    GTS_DECL
    GTS();
    constexpr int NKB = MODE == 0 ? 8 : FF / 64;
    extern __shared__ uint8_t smem_raw[];
    const uint32_t s0 = (smem_u32(smem_raw) + 1023) & ~1023u;
    const uint32_t sStg = s0 + GS_ST * GS_STAGE, full = sStg + 16384, empty = full + 8 * GS_ST;
    const int warp = __shfl_sync(0xffffffffu, threadIdx.x >> 5, 0);
    const int lane = threadIdx.x & 31;
    const uint32_t rank = cluster_ctarank();
    const int rb = blockIdx.x >> 3, nt = blockIdx.x & 7;
    if (warp == 0 && elect_one()) {
        for (int i = 0; i < GS_ST; i++) { mbar_init(full + 8 * i, 1); mbar_init(empty + 8 * i, 4); }
        fence_mbar_init();
        fence_proxy_async();
        for (int kb = 0; kb < GS_ST; kb++) {
            mbar_expect_tx(full + 8 * kb, GS_STAGE);
            tma_load_2d(s0 + kb * GS_STAGE + 16384, &mW, full + 8 * kb, nt * 64, kb * 64);
        }
        prefetch_tmap(&mA); prefetch_tmap(&mOut);
    }
    __syncthreads();
    cluster_sync_relaxed();
    pdl_launch();
    if (warp < 4) {
        if (warp == 0 && elect_one()) {
            pdl_wait();
            if (true) { TL_MARK((MODE == 0 ? 4 : 6)); }
            int s = 0, ph = 1;
            for (int kb = 0; kb < NKB; kb++) {
                const uint32_t st = s0 + s * GS_STAGE;
                if (kb >= GS_ST) {
                    mbar_wait(empty + 8 * s, ph);
                    mbar_expect_tx(full + 8 * s, GS_STAGE);
                    tma_load_2d(st + 16384, &mW, full + 8 * s, nt * 64, kb * 64);
                }
                int shift = 0;
                if (MODE == 0) { const int g = kb >> 1; shift = g == 0 ? -1 : (g == 1 ? 1 : (g == 2 ? -2 : 2)); }
                tma_load_2d_mc(st + rank * 8192, &mA, full + 8 * s, kb * 64, rb * 128 + rank * 64 + shift, (uint16_t)3);
                if (++s == GS_ST) { s = 0; ph ^= 1; }
            }
            if (NKB > GS_ST) for (int i = 0; i < GS_ST; i++) { mbar_wait(empty + 8 * s, ph); if (++s == GS_ST) { s = 0; ph ^= 1; } }
        }
    } else {
        const int w = (warp >> 2) - 1, wq = warp & 3;
        pdl_wait();
        const int row0 = rb * 128 + w * 64 + wq * 16 + (lane >> 2), col0 = nt * 64 + (lane & 3) * 2;
        uint32_t ra[16], rb2[16];
        #pragma unroll
        for (int j = 0; j < 8; j++) {
            ra[2 * j] = __ldcg(reinterpret_cast<const uint32_t*>(h + (size_t)row0 * DM + col0 + j * 8));
            ra[2 * j + 1] = __ldcg(reinterpret_cast<const uint32_t*>(h + (size_t)(row0 + 8) * DM + col0 + j * 8));
        }
        float2 st0, st1;
        if (MODE == 0) { st0 = __ldcg(stats + row0); st1 = __ldcg(stats + row0 + 8); }
        else {
            #pragma unroll
            for (int j = 0; j < 8; j++) {
                rb2[2 * j] = __ldcg(reinterpret_cast<const uint32_t*>(x1 + (size_t)row0 * DM + col0 + j * 8));
                rb2[2 * j + 1] = __ldcg(reinterpret_cast<const uint32_t*>(x1 + (size_t)(row0 + 8) * DM + col0 + j * 8));
            }
        }
        float acc[32];
        int s = 0, ph = 0;
        for (int kb = 0; kb < NKB; kb++) {
            mbar_wait(full + 8 * s, ph);
            if (kb == 0) GTS();
            const uint32_t st = s0 + s * GS_STAGE;
            const uint64_t dA = make_desc(st + w * 8192, 16, 1024), dB = make_desc(st + 16384, 8192, 1024);
            wgmma_fence();
            #pragma unroll
            for (int k = 0; k < 4; k++) wgmma_ss_n64<0, 1>(acc, desc_add(dA, k * 32), desc_add(dB, k * 2048), (kb | k) != 0);
            wgmma_commit();
            if (NKB > GS_ST) {
                wgmma_wait<1>();
                if (kb > 0) { const int sp = s == 0 ? GS_ST - 1 : s - 1; if (wq < 2 && lane == 0) mbar_arrive_cta(empty + 8 * sp, wq); }
            }
            if (++s == GS_ST) { s = 0; ph ^= 1; }
        }
        wgmma_wait<0>();
        fence_regs(acc);
        GTS();
        if (NKB > GS_ST) { const int sp = s == 0 ? GS_ST - 1 : s - 1; if (wq < 2 && lane == 0) mbar_arrive_cta(empty + 8 * sp, wq); }
        #pragma unroll
        for (int j = 0; j < 8; j++) {
            float r0 = bf_lo(ra[2 * j]), r1 = bf_hi(ra[2 * j]), r2 = bf_lo(ra[2 * j + 1]), r3 = bf_hi(ra[2 * j + 1]);
            if (MODE == 0) {
                r0 = (r0 - st0.x) * st0.y; r1 = (r1 - st0.x) * st0.y; r2 = (r2 - st1.x) * st1.y; r3 = (r3 - st1.x) * st1.y;
            } else {
                r0 += bf_lo(rb2[2 * j]); r1 += bf_hi(rb2[2 * j]); r2 += bf_lo(rb2[2 * j + 1]); r3 += bf_hi(rb2[2 * j + 1]);
            }
            acc[4 * j] += r0; acc[4 * j + 1] += r1; acc[4 * j + 2] += r2; acc[4 * j + 3] += r3;
        }
        const int r = (lane & 7) + ((lane >> 3) & 1) * 8;
        const uint32_t rowa = sStg + w * 8192 + (wq * 16 + r) * 128;
        #pragma unroll
        for (int j = 0; j < 8; j += 2) {
            const int cg = j + (lane >> 4);
            stmatrix_x4(rowa + ((cg ^ (lane & 7)) << 4),
                pack_bf16(acc[4 * j], acc[4 * j + 1]), pack_bf16(acc[4 * j + 2], acc[4 * j + 3]),
                pack_bf16(acc[4 * j + 4], acc[4 * j + 5]), pack_bf16(acc[4 * j + 6], acc[4 * j + 7]));
        }
        if (MODE == 0) {
            float a0 = 0.f, q0 = 0.f, a1 = 0.f, q1 = 0.f;
            #pragma unroll
            for (int j = 0; j < 8; j++) {
                a0 += acc[4 * j] + acc[4 * j + 1]; q0 = fmaf(acc[4 * j], acc[4 * j], fmaf(acc[4 * j + 1], acc[4 * j + 1], q0));
                a1 += acc[4 * j + 2] + acc[4 * j + 3]; q1 = fmaf(acc[4 * j + 2], acc[4 * j + 2], fmaf(acc[4 * j + 3], acc[4 * j + 3], q1));
            }
            a0 = quad_sum(a0); q0 = quad_sum(q0); a1 = quad_sum(a1); q1 = quad_sum(q1);
            if ((lane & 3) == 0) {
                atomicAdd(&x1stat[row0].x, a0); atomicAdd(&x1stat[row0].y, q0);
                atomicAdd(&x1stat[row0 + 8].x, a1); atomicAdd(&x1stat[row0 + 8].y, q1);
            }
        }
        bar_sync(3 + w, 128);
        if (wq == 0 && elect_one()) {
            fence_proxy_async();
            tma_store_2d(&mOut, sStg + w * 8192, nt * 64, rb * 128 + w * 64);
            tma_commit();
            GTS();
            tma_wait<0>();
            GTS();
            TL_END((MODE == 0 ? 4 : 6));
        }
        if (MODE == 0) {
        }
    }
}

constexpr int G3_ST = 4;
constexpr int G3_SMEM = 131072 + G3_ST * 16384 + 32768 + 1024 + 128 + 896
;

__global__ void __cluster_dims__(2, 1, 1) __launch_bounds__(384, 1)
k_g3(const __grid_constant__ CUtensorMap mX1, const __grid_constant__ CUtensorMap mW3, const __grid_constant__ CUtensorMap mU,
     const __grid_constant__ CUtensorMap mU32, const float* __restrict__ cs3, const float2* __restrict__ x1stat) {
    TL_START(5);
    GTS_DECL
    GTS();
    extern __shared__ uint8_t smem_raw[];
    const uint32_t sA = (smem_u32(smem_raw) + 1023) & ~1023u;
    const uint32_t sBst = sA + 131072, sStg = sBst + G3_ST * 16384, full = sStg + 32768, empty = full + 8 * G3_ST, afull = empty + 8 * G3_ST, sCs = afull + 64;
    const int warp = __shfl_sync(0xffffffffu, threadIdx.x >> 5, 0);
    const int lane = threadIdx.x & 31;
    const uint32_t rank = cluster_ctarank();
    const int rb = blockIdx.x >> 3, nt = blockIdx.x & 7;
    const int ncol = nt * 224;
    if (warp == 0 && elect_one()) {
        for (int i = 0; i < G3_ST; i++) { mbar_init(full + 8 * i, 1); mbar_init(empty + 8 * i, 2); }
        for (int i = 0; i < 8; i++) mbar_init(afull + 8 * i, 1);
        fence_mbar_init();
        fence_proxy_async();
        for (int kb = 0; kb < G3_ST; kb++) {
            mbar_expect_tx(full + 8 * kb, 16384);
            tma_load_2d(sBst + kb * 16384, &mW3, full + 8 * kb, ncol, kb * 64);
            tma_load_2d(sBst + kb * 16384 + 8192, &mW3, full + 8 * kb, ncol + 64, kb * 64);
        }
        for (int c = 0; c < 8; c++) mbar_expect_tx(afull + 8 * c, 16384);
        prefetch_tmap(&mX1); prefetch_tmap(&mU); prefetch_tmap(&mU32);
    }
    __syncthreads();
    cluster_sync_relaxed();
    pdl_launch();
    if (warp < 4) {
        reg_dealloc<40>();
        if (warp == 0 && elect_one()) {
            pdl_wait();
            if (true) { TL_MARK(5); }
            for (int c = 0; c < 8; c++)
                tma_load_2d_mc(sA + c * 16384 + rank * 8192, &mX1, afull + 8 * c, c * 64, rb * 128 + rank * 64, (uint16_t)3);
            int s = 0, ph = 0;
            for (int i = G3_ST; i < 16; i++) {
                const int t = i >> 3, kb = i & 7;
                mbar_wait(empty + 8 * s, ph);
                mbar_expect_tx(full + 8 * s, 16384);
                tma_load_2d(sBst + s * 16384, &mW3, full + 8 * s, ncol + t * 128, kb * 64);
                tma_load_2d(sBst + s * 16384 + 8192, &mW3, full + 8 * s, ncol + t * 128 + 64, kb * 64);
                if (++s == G3_ST) { s = 0; ph ^= 1; }
            }
        }
    } else {
        reg_alloc<232>();
        const int w = (warp >> 2) - 1, wq = warp & 3;
#define STS_TS()
        float acc0[64], acc1[48];
        float sc0, sc1, mean0, mean1;
        pdl_wait();
        {
            const int ct = threadIdx.x - 128;
            if (ct < 224) { const float v = __ldcg(cs3 + ncol + ct); asm volatile("st.shared.f32 [%0], %1;" :: "r"(sCs + 4 * ct), "f"(v) : "memory"); }
            const int row0 = rb * 128 + w * 64 + wq * 16 + (lane >> 2);
            const float2 s0 = __ldcg(x1stat + row0), s1 = __ldcg(x1stat + row0 + 8);
            mean0 = s0.x * (1.f / DM); mean1 = s1.x * (1.f / DM);
            sc0 = 0.5f * rsqrtf(fmaxf(s0.y * (1.f / DM) - mean0 * mean0, 0.f) + LN_EPS);
            sc1 = 0.5f * rsqrtf(fmaxf(s1.y * (1.f / DM) - mean1 * mean1, 0.f) + LN_EPS);
            bar_sync(1, 256);
        }
        int s = 0, ph = 0;
        const uint64_t dA = make_desc(sA + w * 8192, 16, 1024);
        const int r = (lane & 7) + ((lane >> 3) & 1) * 8;
        const uint32_t stg = sStg + w * 16384, stg1 = sBst + w * 16384;
        const uint32_t csa = sCs + (lane & 3) * 8;
        auto ldcs = [&](int col) { float2 v; asm volatile("ld.shared.v2.f32 {%0, %1}, [%2];" : "=f"(v.x), "=f"(v.y) : "r"(csa + col * 4)); return v; };
        auto act = [&](const float* a, const float2 c0, const float2 c1, uint32_t (&o)[4]) {
            o[0] = pack_bf16(gelu_half(fmaf(-mean0, c0.x, a[0]) * sc0), gelu_half(fmaf(-mean0, c0.y, a[1]) * sc0));
            o[1] = pack_bf16(gelu_half(fmaf(-mean1, c0.x, a[2]) * sc1), gelu_half(fmaf(-mean1, c0.y, a[3]) * sc1));
            o[2] = pack_bf16(gelu_half(fmaf(-mean0, c1.x, a[4]) * sc0), gelu_half(fmaf(-mean0, c1.y, a[5]) * sc0));
            o[3] = pack_bf16(gelu_half(fmaf(-mean1, c1.x, a[6]) * sc1), gelu_half(fmaf(-mean1, c1.y, a[7]) * sc1));
        };
        auto slice0 = [&](int j2) {
            const int j = 2 * j2, cg = j + (lane >> 4);
            const float2 c0 = ldcs(j * 8), c1 = ldcs(j * 8 + 8);
            uint32_t o[4]; act(&acc0[4 * j], c0, c1, o);
            stmatrix_x4(stg + (wq * 16 + r) * 128 + (cg >> 3) * 8192 + (((cg & 7) ^ (lane & 7)) << 4), o[0], o[1], o[2], o[3]);
        };
        auto slice1 = [&](int j2) {
            const int j = 2 * j2, cg = j + (lane >> 4);
            const float2 c0 = ldcs(128 + j * 8), c1 = ldcs(128 + j * 8 + 8);
            uint32_t o[4]; act(&acc1[4 * j], c0, c1, o);
            const int row = wq * 16 + r;
            const uint32_t a = (j2 < 4) ? stg1 + row * 128 + ((cg ^ (lane & 7)) << 4)
                                        : stg1 + 8192 + row * 64 + (((cg - 8) ^ ((row >> 1) & 3)) << 4);
            stmatrix_x4(a, o[0], o[1], o[2], o[3]);
        };
        #pragma unroll
        for (int i = 0; i < 16; i++) {
            const int t = i >> 3, kb = i & 7;
            STS_TS();
            if (t == 0) mbar_wait(afull + 8 * kb, 0);
            STS_TS();
            mbar_wait(full + 8 * s, ph);
            STS_TS();
            const uint64_t dB = make_desc(sBst + s * 16384, 8192, 1024);
            wgmma_fence();
            #pragma unroll
            for (int k = 0; k < 4; k++) {
                if (t == 0) wgmma_ss_n128<0, 1>(acc0, desc_add(dA, kb * 16384 + k * 32), desc_add(dB, k * 2048), (kb | k) != 0);
                else        wgmma_ss_n96<0, 1>(acc1, desc_add(dA, kb * 16384 + k * 32), desc_add(dB, k * 2048), (kb | k) != 0);
            }
            wgmma_commit();
            STS_TS();
            STS_TS();
            wgmma_wait<1>();
            STS_TS();
            if (i > 0) { const int sp = s == 0 ? G3_ST - 1 : s - 1; mbar_arrive_if(empty + 8 * sp, wq == 0 && lane == 0); }
            if (++s == G3_ST) { s = 0; ph ^= 1; }
            if (t == 1) {
                if (kb == 0) fence_regs(acc0);
                slice0(kb);
                if (kb == 7) {
                    bar_sync(3 + w, 128);
                    if (wq == 0 && elect_one()) {
                        fence_proxy_async();
                        tma_store_2d(&mU, stg, ncol, rb * 128 + w * 64);
                        tma_store_2d(&mU, stg + 8192, ncol + 64, rb * 128 + w * 64);
                        tma_commit();
                    }
                }
            }
        }
        wgmma_wait<0>();
        fence_regs(acc1);
        GTS();
        bar_sync(1, 256);
        #pragma unroll
        for (int j = 0; j < 6; j++) slice1(j);
        bar_sync(3 + w, 128);
        GTS();
        if (wq == 0 && elect_one()) {
            fence_proxy_async();
            tma_store_2d(&mU, stg1, ncol + 128, rb * 128 + w * 64);
            tma_store_2d(&mU32, stg1 + 8192, ncol + 192, rb * 128 + w * 64);
            tma_commit();
            tma_wait<0>();
            GTS();
            TL_END(5);
        }
    }
}
__device__ __align__(1024) bf16  g_qkv[3 * NH * S_LEN * HD];
__device__ __align__(1024) bf16  g_ctx[S_LEN * NH * HD];
__device__ __align__(1024) bf16  g_h[S_LEN * DM];
__device__ __align__(1024) float2 g_stats[S_LEN];
__device__ __align__(1024) float g_colsum[DM + FF];
__device__ __align__(1024) float2 g_x1stat[S_LEN];
__device__ __align__(1024) bf16  g_t1[S_LEN * DM];
__device__ __align__(1024) bf16  g_x1[S_LEN * DM];
__device__ __align__(1024) bf16  g_u[S_LEN * FF];

typedef CUresult (*EncodeTiledFn)(CUtensorMap*, CUtensorMapDataType, cuuint32_t, void*, const cuuint64_t*, const cuuint64_t*,
                                  const cuuint32_t*, const cuuint32_t*, CUtensorMapInterleave, CUtensorMapSwizzle,
                                  CUtensorMapL2promotion, CUtensorMapFloatOOBfill);
static EncodeTiledFn g_encode = nullptr;

static CUtensorMap make_map(const void* ptr, int rank, const uint64_t* dims, const uint64_t* strides, const uint32_t* box,
                            CUtensorMapSwizzle sw = CU_TENSOR_MAP_SWIZZLE_128B) {
    const CUtensorMapDataType dt = CU_TENSOR_MAP_DATA_TYPE_BFLOAT16;
    CUtensorMap m;
    cuuint64_t d[3], st[2]; cuuint32_t b[3], es[3] = {1, 1, 1};
    for (int i = 0; i < rank; i++) { d[i] = dims[i]; b[i] = box[i]; }
    for (int i = 0; i < rank - 1; i++) st[i] = strides[i];
    g_encode(&m, dt, rank, (void*)ptr, d, st, b, es, CU_TENSOR_MAP_INTERLEAVE_NONE, sw,
             CU_TENSOR_MAP_L2_PROMOTION_L2_256B, CU_TENSOR_MAP_FLOAT_OOB_FILL_NONE);
    return m;
}
static CUtensorMap map2d(const void* p, uint64_t cols, uint64_t rows, uint32_t box_cols, uint32_t box_rows) {
    uint64_t d[2] = {cols, rows}, s[1] = {cols * 2}; uint32_t b[2] = {box_cols, box_rows};
    return make_map(p, 2, d, s, b);
}
static CUtensorMap map3d(const void* p, uint64_t cols, uint64_t rows, uint32_t box_rows, uint32_t nchunks) {
    uint64_t d[3] = {64, rows, cols / 64}, s[2] = {cols * 2, 128}; uint32_t b[3] = {64, box_rows, nchunks};
    return make_map(p, 3, d, s, b);
}

template<typename... KArgs, typename... Args>
static void launch(void (*kern)(KArgs...), int grid, int smem, cudaStream_t st, bool pdl, Args... args) {
    cudaLaunchConfig_t cfg = {};
    cfg.gridDim = dim3(grid); cfg.blockDim = dim3(384); cfg.dynamicSmemBytes = smem; cfg.stream = st;
    cudaLaunchAttribute at[1];
    at[0].id = cudaLaunchAttributeProgrammaticStreamSerialization;
    at[0].val.programmaticStreamSerializationAllowed = 1;
    cfg.attrs = at; cfg.numAttrs = pdl ? 1 : 0;
    cudaLaunchKernelEx(&cfg, kern, KArgs(args)...);
}

#define USE_PDL 1

struct Plan {
    CUtensorMap mX, mC, mWq, mWk, mWv, mQkvOut, mQkvIn, mCtxOut, mCtxIn, mWo, mH, mW1, mT1out, mT1in, mW2, mX1out, mX1in, mW3, mU, mU32, mUin, mW4, mOut;
    bf16 *qkv, *ctx, *t1, *x1, *u, *h; float2 *stats, *x1stat; float* colsum;
};

static void build_plan(Plan& p, void* const* d_in, void* d_out) {
    if (!g_encode) {
        void* fn = nullptr; cudaDriverEntryPointQueryResult qr;
        cudaGetDriverEntryPoint("cuTensorMapEncodeTiled", &fn, cudaEnableDefault, &qr);
        g_encode = (EncodeTiledFn)fn;
        cudaFuncSetAttribute(k_qkv, cudaFuncAttributeMaxDynamicSharedMemorySize, QK_SMEM);
        cudaFuncSetAttribute(k_attn, cudaFuncAttributeMaxDynamicSharedMemorySize, AT_SMEM);
        cudaFuncSetAttribute(k_oproj, cudaFuncAttributeMaxDynamicSharedMemorySize, GO_SMEM);
        cudaFuncSetAttribute(k_g1, cudaFuncAttributeMaxDynamicSharedMemorySize, G1_SMEM);
        cudaFuncSetAttribute(k_gs<0>, cudaFuncAttributeMaxDynamicSharedMemorySize, GS_SMEM);
        cudaFuncSetAttribute(k_gs<1>, cudaFuncAttributeMaxDynamicSharedMemorySize, GS_SMEM);
        cudaFuncSetAttribute(k_g3, cudaFuncAttributeMaxDynamicSharedMemorySize, G3_SMEM);
    }
    cudaGetSymbolAddress((void**)&p.qkv, g_qkv); cudaGetSymbolAddress((void**)&p.ctx, g_ctx);
    cudaGetSymbolAddress((void**)&p.h, g_h); cudaGetSymbolAddress((void**)&p.stats, g_stats); cudaGetSymbolAddress((void**)&p.colsum, g_colsum); cudaGetSymbolAddress((void**)&p.x1stat, g_x1stat);
    cudaGetSymbolAddress((void**)&p.t1, g_t1); cudaGetSymbolAddress((void**)&p.x1, g_x1); cudaGetSymbolAddress((void**)&p.u, g_u);
    p.mX = map2d(d_in[0], DM, S_LEN, 64, 128);
    p.mC = map2d(d_in[1], DM, S_LEN, 64, 128);
    p.mWq = map2d(d_in[2], NH * HD, DM, 64, 64);
    p.mWk = map2d(d_in[3], NH * HD, DM, 64, 64);
    p.mWv = map2d(d_in[4], NH * HD, DM, 64, 64);
    p.mQkvOut = map2d(p.qkv, HD, 3 * NH * S_LEN, 64, 64);
    p.mQkvIn = map3d(p.qkv, HD, 3 * NH * S_LEN, 128, 2);
    p.mCtxOut = map2d(p.ctx, NH * HD, S_LEN, 64, 64);
    p.mCtxIn = map2d(p.ctx, NH * HD, S_LEN, 64, 128);
    p.mWo = map3d(d_in[5], DM, NH * HD, 64, 2);
    p.mH = map2d(p.h, DM, S_LEN, 64, 64);
    p.mW1 = map3d(d_in[7], DM, DM, 64, 2);
    p.mT1out = map2d(p.t1, DM, S_LEN, 64, 64);
    p.mT1in = map2d(p.t1, DM, S_LEN, 64, 64);
    p.mW2 = map2d(d_in[8], DM, DM, 64, 64);
    p.mX1out = map2d(p.x1, DM, S_LEN, 64, 64);
    p.mX1in = map2d(p.x1, DM, S_LEN, 64, 64);
    p.mW3 = map2d(d_in[9], FF, DM, 64, 64);
    p.mU = map2d(p.u, FF, S_LEN, 64, 64);
    { uint64_t d[2] = {FF, S_LEN}, s[1] = {FF * 2}; uint32_t b[2] = {32, 64};
      p.mU32 = make_map(p.u, 2, d, s, b, CU_TENSOR_MAP_SWIZZLE_64B); }
    p.mUin = map2d(p.u, FF, S_LEN, 64, 64);
    p.mW4 = map2d(d_in[10], DM, FF, 64, 64);
    p.mOut = map2d(d_out, DM, S_LEN, 64, 64);
}

static void run_stage(const Plan& p, int stage, void* const* d_in, cudaStream_t st, bool pdl) {
    switch (stage) {
    case 0: launch(k_qkv, 128, QK_SMEM, st, false, p.mX, p.mC, p.mWq, p.mWk, p.mWv, p.mQkvOut, (const bf16*)d_in[0], p.h, (const bf16*)d_in[2], (const bf16*)d_in[3], (const bf16*)d_in[4]); break;
    case 1: {
        PrefetchList pf;
        pf.ptr[0] = d_in[5]; pf.bytes[0] = NH * HD * DM * 2;
        pf.ptr[1] = d_in[7]; pf.bytes[1] = DM * DM * 2;
        pf.ptr[2] = d_in[8]; pf.bytes[2] = DM * DM * 2;
        pf.ptr[3] = d_in[9]; pf.bytes[3] = DM * FF * 2;
        pf.ptr[4] = d_in[10]; pf.bytes[4] = DM * FF * 2;
        pf.colsum = p.colsum;
        launch(k_attn, 132, AT_SMEM, st, pdl, p.mQkvIn, p.mCtxOut, pf, (const bf16*)p.qkv); break; }
    case 2: launch(k_oproj, 128, GO_SMEM, st, pdl, p.mCtxIn, p.mWo, p.mH); break;
    case 3: launch(k_g1, 128, G1_SMEM, st, pdl, p.mH, p.mW1, p.mT1out, p.stats, (const float*)p.colsum, p.x1stat); break;
    case 4: launch(k_gs<0>, 128, GS_SMEM, st, pdl, p.mT1in, p.mW2, p.mX1out, (const bf16*)p.h, (const float2*)p.stats, (const bf16*)nullptr, p.x1stat); break;
    case 5: launch(k_g3, 128, G3_SMEM, st, pdl, p.mX1in, p.mW3, p.mU, p.mU32, (const float*)(p.colsum + DM), (const float2*)p.x1stat); break;
    case 6: launch(k_gs<1>, 128, GS_SMEM, st, pdl, p.mUin, p.mW4, p.mOut, (const bf16*)p.h, (const float2*)p.stats, (const bf16*)p.x1, p.x1stat); break;
    }
}

constexpr int NUM_STAGES = 7;
extern "C" void kernel_launch(void* const* d_in, const int* in_sizes, int n_in, void* d_out, int out_size) {
    Plan p;
    build_plan(p, d_in, d_out);
    cudaStream_t st = cudaStreamPerThread;
    for (int s = 0; s < NUM_STAGES; s++) run_stage(p, s, d_in, st, USE_PDL);
}
```

```cpp
#include <cuda_runtime.h>
#include <cuda_bf16.h>
#include <cuda.h>
#include <stdint.h>

typedef __nv_bfloat16 bf16;

constexpr int S_LEN = 2048;
constexpr int DM    = 512;
constexpr int NH    = 32;
constexpr int HD    = 128;
constexpr int FF    = 1792;
constexpr float LN_EPS = 1e-5f;
constexpr float AT_SCALE = 0.08838834764831845f * 1.4426950408889634f;

#define GTS_DECL
#define GTS()
#define PROF_DECL
#define PROF_TS(slot)
#define TL_START(k)
#define TL_MARK(k)
#define TL_END(k)
#define TL_FIRST(k)
#define SPIN_LIMIT (1u << 20)

__device__ __forceinline__ uint32_t smem_u32(const void* p) { return (uint32_t)__cvta_generic_to_shared(p); }
__device__ __forceinline__ uint32_t elect_one() {
    uint32_t pred;
    asm volatile("{\n.reg .pred px;\nelect.sync _|px, 0xFFFFFFFF;\nselp.u32 %0, 1, 0, px;\n}\n" : "=r"(pred));
    return pred;
}
__device__ __forceinline__ void mbar_init(uint32_t bar, uint32_t count) {
    asm volatile("mbarrier.init.shared::cta.b64 [%0], %1;" :: "r"(bar), "r"(count) : "memory");
}
__device__ __forceinline__ void mbar_expect_tx(uint32_t bar, uint32_t bytes) {
    asm volatile("mbarrier.arrive.expect_tx.shared::cta.b64 _, [%0], %1;" :: "r"(bar), "r"(bytes) : "memory");
}
__device__ __forceinline__ void mbar_arrive(uint32_t bar) {
    asm volatile("mbarrier.arrive.shared::cta.b64 _, [%0];" :: "r"(bar) : "memory");
}
__device__ __forceinline__ void mbar_arrive_if(uint32_t bar, uint32_t flag) {
    asm volatile("{\n.reg .pred p;\nsetp.ne.b32 p, %1, 0;\n@p mbarrier.arrive.shared::cta.b64 _, [%0];\n}" :: "r"(bar), "r"(flag) : "memory");
}
__device__ __forceinline__ void mbar_arrive_cta(uint32_t bar, uint32_t cta) {
    asm volatile("{\n.reg .b32 ra;\nmapa.shared::cluster.u32 ra, %0, %1;\n"
                 "mbarrier.arrive.shared::cluster.b64 _, [ra];\n}" :: "r"(bar), "r"(cta) : "memory");
}
__device__ __forceinline__ bool mbar_try_wait(uint32_t bar, uint32_t parity) {
    uint32_t ok;
    asm volatile("{\n.reg .pred p;\nmbarrier.try_wait.parity.shared::cta.b64 p, [%1], %2;\nselp.u32 %0, 1, 0, p;\n}"
                 : "=r"(ok) : "r"(bar), "r"(parity) : "memory");
    return ok;
}
__device__ __forceinline__ bool mbar_test(uint32_t bar, uint32_t parity) {
    uint32_t ok;
    asm volatile("{\n.reg .pred p;\nmbarrier.test_wait.parity.shared::cta.b64 p, [%1], %2;\nselp.u32 %0, 1, 0, p;\n}"
                 : "=r"(ok) : "r"(bar), "r"(parity) : "memory");
    return ok;
}
__device__ __forceinline__ void mbar_wait(uint32_t bar, uint32_t parity) {
    uint32_t n = 0;
    while (!mbar_try_wait(bar, parity) && ++n < SPIN_LIMIT) { }
}
__device__ __forceinline__ bool mbar_try_wait_cl(uint32_t bar, uint32_t parity) {
    uint32_t ok;
    asm volatile("{\n.reg .pred p;\nmbarrier.try_wait.parity.shared::cta.b64 p, [%1], %2;\nselp.u32 %0, 1, 0, p;\n}"
                 : "=r"(ok) : "r"(bar), "r"(parity) : "memory");
    return ok;
}
__device__ __forceinline__ void mbar_wait_cl(uint32_t bar, uint32_t parity) {
    uint32_t n = 0;
    while (!mbar_try_wait_cl(bar, parity) && ++n < SPIN_LIMIT) { }
}
__device__ __forceinline__ void fence_mbar_init() { asm volatile("fence.mbarrier_init.release.cluster;" ::: "memory"); }
__device__ __forceinline__ void fence_proxy_async() { asm volatile("fence.proxy.async.shared::cta;" ::: "memory"); }
__device__ __forceinline__ void fence_proxy_async_all() { asm volatile("fence.proxy.async;" ::: "memory"); }

__device__ __forceinline__ void tma_load_2d(uint32_t dst, const CUtensorMap* map, uint32_t bar, int c0, int c1) {
    asm volatile("cp.async.bulk.tensor.2d.shared::cluster.global.mbarrier::complete_tx::bytes [%0], [%1, {%3, %4}], [%2];"
        :: "r"(dst), "l"(map), "r"(bar), "r"(c0), "r"(c1) : "memory");
}
__device__ __forceinline__ void tma_load_3d(uint32_t dst, const CUtensorMap* map, uint32_t bar, int c0, int c1, int c2) {
    asm volatile("cp.async.bulk.tensor.3d.shared::cluster.global.mbarrier::complete_tx::bytes [%0], [%1, {%3, %4, %5}], [%2];"
        :: "r"(dst), "l"(map), "r"(bar), "r"(c0), "r"(c1), "r"(c2) : "memory");
}
__device__ __forceinline__ void tma_load_2d_mc(uint32_t dst, const CUtensorMap* map, uint32_t bar, int c0, int c1, uint16_t mask) {
    asm volatile("cp.async.bulk.tensor.2d.shared::cluster.global.mbarrier::complete_tx::bytes.multicast::cluster [%0], [%1, {%3, %4}], [%2], %5;"
        :: "r"(dst), "l"(map), "r"(bar), "r"(c0), "r"(c1), "h"(mask) : "memory");
}
__device__ __forceinline__ void tma_load_3d_mc(uint32_t dst, const CUtensorMap* map, uint32_t bar, int c0, int c1, int c2, uint16_t mask) {
    asm volatile("cp.async.bulk.tensor.3d.shared::cluster.global.mbarrier::complete_tx::bytes.multicast::cluster [%0], [%1, {%3, %4, %5}], [%2], %6;"
        :: "r"(dst), "l"(map), "r"(bar), "r"(c0), "r"(c1), "r"(c2), "h"(mask) : "memory");
}
__device__ __forceinline__ void tma_store_2d(const CUtensorMap* map, uint32_t src, int c0, int c1) {
    asm volatile("cp.async.bulk.tensor.2d.global.shared::cta.bulk_group [%0, {%2, %3}], [%1];"
        :: "l"(map), "r"(src), "r"(c0), "r"(c1) : "memory");
}
__device__ __forceinline__ void tma_store_2d_hint(const CUtensorMap* map, uint32_t src, int c0, int c1, uint64_t pol) {
    asm volatile("cp.async.bulk.tensor.2d.global.shared::cta.bulk_group.L2::cache_hint [%0, {%2, %3}], [%1], %4;"
        :: "l"(map), "r"(src), "r"(c0), "r"(c1), "l"(pol) : "memory");
}
__device__ __forceinline__ uint64_t policy_evict_first() {
    uint64_t p; asm volatile("createpolicy.fractional.L2::evict_first.b64 %0, 1.0;" : "=l"(p)); return p;
}
__device__ __forceinline__ void tma_store_3d(const CUtensorMap* map, uint32_t src, int c0, int c1, int c2) {
    asm volatile("cp.async.bulk.tensor.3d.global.shared::cta.bulk_group [%0, {%2, %3, %4}], [%1];"
        :: "l"(map), "r"(src), "r"(c0), "r"(c1), "r"(c2) : "memory");
}
__device__ __forceinline__ void tma_red_add_2d(const CUtensorMap* map, uint32_t src, int c0, int c1) {
    asm volatile("cp.reduce.async.bulk.tensor.2d.global.shared::cta.add.bulk_group [%0, {%2, %3}], [%1];"
        :: "l"(map), "r"(src), "r"(c0), "r"(c1) : "memory");
}
__device__ __forceinline__ void tma_prefetch_2d(const CUtensorMap* map, int c0, int c1) {
    asm volatile("cp.async.bulk.prefetch.tensor.2d.L2.global [%0, {%1, %2}];" :: "l"(map), "r"(c0), "r"(c1) : "memory");
}
__device__ __forceinline__ void l2_prefetch(const void* p, uint32_t bytes) {
    asm volatile("cp.async.bulk.prefetch.L2.global [%0], %1;" :: "l"(p), "r"(bytes) : "memory");
}
__device__ __forceinline__ void prefetch_l2(const void* p) { asm volatile("prefetch.global.L2 [%0];" :: "l"(p)); }
__device__ __forceinline__ void tma_commit() { asm volatile("cp.async.bulk.commit_group;" ::: "memory"); }
template<int N> __device__ __forceinline__ void tma_wait_read() { asm volatile("cp.async.bulk.wait_group.read %0;" :: "n"(N) : "memory"); }
template<int N> __device__ __forceinline__ void tma_wait() { asm volatile("cp.async.bulk.wait_group %0;" :: "n"(N) : "memory"); }
__device__ __forceinline__ void prefetch_tmap(const CUtensorMap* map) {
    asm volatile("prefetch.tensormap [%0];" :: "l"(map) : "memory");
}

__device__ __forceinline__ void wgmma_fence() { asm volatile("wgmma.fence.sync.aligned;" ::: "memory"); }
__device__ __forceinline__ void wgmma_commit() { asm volatile("wgmma.commit_group.sync.aligned;" ::: "memory"); }
template<int N> __device__ __forceinline__ void wgmma_wait() { asm volatile("wgmma.wait_group.sync.aligned %0;" :: "n"(N) : "memory"); }

template<int N> __device__ __forceinline__ void fence_regs(float (&d)[N]) {
    #pragma unroll
    for (int i = 0; i < N; i++) asm volatile("" : "+f"(d[i]) :: "memory");
}
template<int N> __device__ __forceinline__ void fence_regs(uint32_t (&d)[N]) {
    #pragma unroll
    for (int i = 0; i < N; i++) asm volatile("" : "+r"(d[i]) :: "memory");
}

__device__ __forceinline__ uint64_t make_desc(uint32_t addr, uint32_t lbo_bytes, uint32_t sbo_bytes) {
    uint64_t d = 0;
    d |= (uint64_t)((addr & 0x3FFFF) >> 4);
    d |= (uint64_t)((lbo_bytes & 0x3FFFF) >> 4) << 16;
    d |= (uint64_t)((sbo_bytes & 0x3FFFF) >> 4) << 32;
    d |= (uint64_t)1 << 62;
    return d;
}
__device__ __forceinline__ uint64_t desc_add(uint64_t d, uint32_t bytes) {
    return d + (uint64_t)(bytes >> 4);
}

__device__ __forceinline__ void bar_sync(int id, int n) { asm volatile("bar.sync %0, %1;" :: "r"(id), "r"(n) : "memory"); }
__device__ __forceinline__ void bar_arrive(int id, int n) { asm volatile("bar.arrive %0, %1;" :: "r"(id), "r"(n) : "memory"); }
__device__ __forceinline__ bool bar_red_or(int id, int n, bool v) {
    uint32_t r;
    asm volatile("{\n.reg .pred p, q;\nsetp.ne.u32 q, %3, 0;\nbar.red.or.pred p, %1, %2, q;\nselp.u32 %0, 1, 0, p;\n}"
                 : "=r"(r) : "r"(id), "r"(n), "r"((uint32_t)v) : "memory");
    return r;
}
template<int R> __device__ __forceinline__ void reg_alloc() { asm volatile("setmaxnreg.inc.sync.aligned.u32 %0;" :: "n"(R)); }
template<int R> __device__ __forceinline__ void reg_dealloc() { asm volatile("setmaxnreg.dec.sync.aligned.u32 %0;" :: "n"(R)); }
__device__ __forceinline__ uint32_t cluster_ctarank() { uint32_t r; asm volatile("mov.u32 %0, %%cluster_ctarank;" : "=r"(r)); return r; }
__device__ __forceinline__ void cluster_arrive() { asm volatile("barrier.cluster.arrive.release.aligned;" ::: "memory"); }
__device__ __forceinline__ void cluster_wait() { asm volatile("barrier.cluster.wait.acquire.aligned;" ::: "memory"); }
__device__ __forceinline__ void pdl_wait() { asm volatile("griddepcontrol.wait;" ::: "memory"); }
__device__ __forceinline__ void pdl_launch() { asm volatile("griddepcontrol.launch_dependents;" ::: "memory"); }

__device__ __forceinline__ uint32_t pack_bf16(float lo, float hi) {
    uint32_t r;
    asm("cvt.rn.bf16x2.f32 %0, %1, %2;" : "=r"(r) : "f"(hi), "f"(lo));
    return r;
}
__device__ __forceinline__ float ex2(float x) {
    float y;
    asm("ex2.approx.ftz.f32 %0, %1;" : "=f"(y) : "f"(x));
    return y;
}
__device__ __forceinline__ void stmatrix_x4(uint32_t addr, uint32_t r0, uint32_t r1, uint32_t r2, uint32_t r3) {
    asm volatile("stmatrix.sync.aligned.m8n8.x4.shared.b16 [%0], {%1, %2, %3, %4};"
        :: "r"(addr), "r"(r0), "r"(r1), "r"(r2), "r"(r3) : "memory");
}
template<int TA, int TB> __device__ __forceinline__ void wgmma_ss_n128(float (&d)[64], uint64_t descA, uint64_t descB, int scaleD) {
    asm volatile("{\n.reg .pred p;\n"
        "setp.ne.b32 p, %66, 0;\n"
        "wgmma.mma_async.sync.aligned.m64n128k16.f32.bf16.bf16 "
        "{%0,%1,%2,%3,%4,%5,%6,%7,%8,%9,%10,%11,%12,%13,%14,%15,%16,%17,%18,%19,%20,%21,%22,%23,%24,%25,%26,%27,%28,%29,%30,%31,%32,%33,%34,%35,%36,%37,%38,%39,%40,%41,%42,%43,%44,%45,%46,%47,%48,%49,%50,%51,%52,%53,%54,%55,%56,%57,%58,%59,%60,%61,%62,%63}, "
        "%64, %65, p, 1, 1, %67, %68;\n}\n"
        : "+f"(d[0]),"+f"(d[1]),"+f"(d[2]),"+f"(d[3]),"+f"(d[4]),"+f"(d[5]),"+f"(d[6]),"+f"(d[7]),"+f"(d[8]),"+f"(d[9]),"+f"(d[10]),"+f"(d[11]),"+f"(d[12]),"+f"(d[13]),"+f"(d[14]),"+f"(d[15]),"+f"(d[16]),"+f"(d[17]),"+f"(d[18]),"+f"(d[19]),"+f"(d[20]),"+f"(d[21]),"+f"(d[22]),"+f"(d[23]),"+f"(d[24]),"+f"(d[25]),"+f"(d[26]),"+f"(d[27]),"+f"(d[28]),"+f"(d[29]),"+f"(d[30]),"+f"(d[31]),"+f"(d[32]),"+f"(d[33]),"+f"(d[34]),"+f"(d[35]),"+f"(d[36]),"+f"(d[37]),"+f"(d[38]),"+f"(d[39]),"+f"(d[40]),"+f"(d[41]),"+f"(d[42]),"+f"(d[43]),"+f"(d[44]),"+f"(d[45]),"+f"(d[46]),"+f"(d[47]),"+f"(d[48]),"+f"(d[49]),"+f"(d[50]),"+f"(d[51]),"+f"(d[52]),"+f"(d[53]),"+f"(d[54]),"+f"(d[55]),"+f"(d[56]),"+f"(d[57]),"+f"(d[58]),"+f"(d[59]),"+f"(d[60]),"+f"(d[61]),"+f"(d[62]),"+f"(d[63])
        : "l"(descA), "l"(descB), "r"(scaleD), "n"(TA), "n"(TB));
}
template<int TB> __device__ __forceinline__ void wgmma_rs_n128(float (&d)[64], uint32_t a0, uint32_t a1, uint32_t a2, uint32_t a3, uint64_t descB, int scaleD) {
    asm volatile("{\n.reg .pred p;\n"
        "setp.ne.b32 p, %69, 0;\n"
        "wgmma.mma_async.sync.aligned.m64n128k16.f32.bf16.bf16 "
        "{%0,%1,%2,%3,%4,%5,%6,%7,%8,%9,%10,%11,%12,%13,%14,%15,%16,%17,%18,%19,%20,%21,%22,%23,%24,%25,%26,%27,%28,%29,%30,%31,%32,%33,%34,%35,%36,%37,%38,%39,%40,%41,%42,%43,%44,%45,%46,%47,%48,%49,%50,%51,%52,%53,%54,%55,%56,%57,%58,%59,%60,%61,%62,%63}, "
        "{%64,%65,%66,%67}, %68, p, 1, 1, %70;\n}\n"
        : "+f"(d[0]),"+f"(d[1]),"+f"(d[2]),"+f"(d[3]),"+f"(d[4]),"+f"(d[5]),"+f"(d[6]),"+f"(d[7]),"+f"(d[8]),"+f"(d[9]),"+f"(d[10]),"+f"(d[11]),"+f"(d[12]),"+f"(d[13]),"+f"(d[14]),"+f"(d[15]),"+f"(d[16]),"+f"(d[17]),"+f"(d[18]),"+f"(d[19]),"+f"(d[20]),"+f"(d[21]),"+f"(d[22]),"+f"(d[23]),"+f"(d[24]),"+f"(d[25]),"+f"(d[26]),"+f"(d[27]),"+f"(d[28]),"+f"(d[29]),"+f"(d[30]),"+f"(d[31]),"+f"(d[32]),"+f"(d[33]),"+f"(d[34]),"+f"(d[35]),"+f"(d[36]),"+f"(d[37]),"+f"(d[38]),"+f"(d[39]),"+f"(d[40]),"+f"(d[41]),"+f"(d[42]),"+f"(d[43]),"+f"(d[44]),"+f"(d[45]),"+f"(d[46]),"+f"(d[47]),"+f"(d[48]),"+f"(d[49]),"+f"(d[50]),"+f"(d[51]),"+f"(d[52]),"+f"(d[53]),"+f"(d[54]),"+f"(d[55]),"+f"(d[56]),"+f"(d[57]),"+f"(d[58]),"+f"(d[59]),"+f"(d[60]),"+f"(d[61]),"+f"(d[62]),"+f"(d[63])
        : "r"(a0), "r"(a1), "r"(a2), "r"(a3), "l"(descB), "r"(scaleD), "n"(TB));
}
template<int TA, int TB> __device__ __forceinline__ void wgmma_ss_n256(float (&d)[128], uint64_t descA, uint64_t descB, int scaleD) {
    asm volatile("{\n.reg .pred p;\n"
        "setp.ne.b32 p, %130, 0;\n"
        "wgmma.mma_async.sync.aligned.m64n256k16.f32.bf16.bf16 "
        "{%0,%1,%2,%3,%4,%5,%6,%7,%8,%9,%10,%11,%12,%13,%14,%15,%16,%17,%18,%19,%20,%21,%22,%23,%24,%25,%26,%27,%28,%29,%30,%31,%32,%33,%34,%35,%36,%37,%38,%39,%40,%41,%42,%43,%44,%45,%46,%47,%48,%49,%50,%51,%52,%53,%54,%55,%56,%57,%58,%59,%60,%61,%62,%63,%64,%65,%66,%67,%68,%69,%70,%71,%72,%73,%74,%75,%76,%77,%78,%79,%80,%81,%82,%83,%84,%85,%86,%87,%88,%89,%90,%91,%92,%93,%94,%95,%96,%97,%98,%99,%100,%101,%102,%103,%104,%105,%106,%107,%108,%109,%110,%111,%112,%113,%114,%115,%116,%117,%118,%119,%120,%121,%122,%123,%124,%125,%126,%127}, "
        "%128, %129, p, 1, 1, %131, %132;\n}\n"
        : "+f"(d[0]),"+f"(d[1]),"+f"(d[2]),"+f"(d[3]),"+f"(d[4]),"+f"(d[5]),"+f"(d[6]),"+f"(d[7]),"+f"(d[8]),"+f"(d[9]),"+f"(d[10]),"+f"(d[11]),"+f"(d[12]),"+f"(d[13]),"+f"(d[14]),"+f"(d[15]),"+f"(d[16]),"+f"(d[17]),"+f"(d[18]),"+f"(d[19]),"+f"(d[20]),"+f"(d[21]),"+f"(d[22]),"+f"(d[23]),"+f"(d[24]),"+f"(d[25]),"+f"(d[26]),"+f"(d[27]),"+f"(d[28]),"+f"(d[29]),"+f"(d[30]),"+f"(d[31]),"+f"(d[32]),"+f"(d[33]),"+f"(d[34]),"+f"(d[35]),"+f"(d[36]),"+f"(d[37]),"+f"(d[38]),"+f"(d[39]),"+f"(d[40]),"+f"(d[41]),"+f"(d[42]),"+f"(d[43]),"+f"(d[44]),"+f"(d[45]),"+f"(d[46]),"+f"(d[47]),"+f"(d[48]),"+f"(d[49]),"+f"(d[50]),"+f"(d[51]),"+f"(d[52]),"+f"(d[53]),"+f"(d[54]),"+f"(d[55]),"+f"(d[56]),"+f"(d[57]),"+f"(d[58]),"+f"(d[59]),"+f"(d[60]),"+f"(d[61]),"+f"(d[62]),"+f"(d[63]),"+f"(d[64]),"+f"(d[65]),"+f"(d[66]),"+f"(d[67]),"+f"(d[68]),"+f"(d[69]),"+f"(d[70]),"+f"(d[71]),"+f"(d[72]),"+f"(d[73]),"+f"(d[74]),"+f"(d[75]),"+f"(d[76]),"+f"(d[77]),"+f"(d[78]),"+f"(d[79]),"+f"(d[80]),"+f"(d[81]),"+f"(d[82]),"+f"(d[83]),"+f"(d[84]),"+f"(d[85]),"+f"(d[86]),"+f"(d[87]),"+f"(d[88]),"+f"(d[89]),"+f"(d[90]),"+f"(d[91]),"+f"(d[92]),"+f"(d[93]),"+f"(d[94]),"+f"(d[95]),"+f"(d[96]),"+f"(d[97]),"+f"(d[98]),"+f"(d[99]),"+f"(d[100]),"+f"(d[101]),"+f"(d[102]),"+f"(d[103]),"+f"(d[104]),"+f"(d[105]),"+f"(d[106]),"+f"(d[107]),"+f"(d[108]),"+f"(d[109]),"+f"(d[110]),"+f"(d[111]),"+f"(d[112]),"+f"(d[113]),"+f"(d[114]),"+f"(d[115]),"+f"(d[116]),"+f"(d[117]),"+f"(d[118]),"+f"(d[119]),"+f"(d[120]),"+f"(d[121]),"+f"(d[122]),"+f"(d[123]),"+f"(d[124]),"+f"(d[125]),"+f"(d[126]),"+f"(d[127])
        : "l"(descA), "l"(descB), "r"(scaleD), "n"(TA), "n"(TB));
}
template<int TA, int TB> __device__ __forceinline__ void wgmma_ss_n64(float (&d)[32], uint64_t descA, uint64_t descB, int scaleD) {
    asm volatile("{\n.reg .pred p;\n"
        "setp.ne.b32 p, %34, 0;\n"
        "wgmma.mma_async.sync.aligned.m64n64k16.f32.bf16.bf16 "
        "{%0,%1,%2,%3,%4,%5,%6,%7,%8,%9,%10,%11,%12,%13,%14,%15,%16,%17,%18,%19,%20,%21,%22,%23,%24,%25,%26,%27,%28,%29,%30,%31}, "
        "%32, %33, p, 1, 1, %35, %36;\n}\n"
        : "+f"(d[0]),"+f"(d[1]),"+f"(d[2]),"+f"(d[3]),"+f"(d[4]),"+f"(d[5]),"+f"(d[6]),"+f"(d[7]),"+f"(d[8]),"+f"(d[9]),"+f"(d[10]),"+f"(d[11]),"+f"(d[12]),"+f"(d[13]),"+f"(d[14]),"+f"(d[15]),"+f"(d[16]),"+f"(d[17]),"+f"(d[18]),"+f"(d[19]),"+f"(d[20]),"+f"(d[21]),"+f"(d[22]),"+f"(d[23]),"+f"(d[24]),"+f"(d[25]),"+f"(d[26]),"+f"(d[27]),"+f"(d[28]),"+f"(d[29]),"+f"(d[30]),"+f"(d[31])
        : "l"(descA), "l"(descB), "r"(scaleD), "n"(TA), "n"(TB));
}
template<int TA, int TB> __device__ __forceinline__ void wgmma_ss_n96(float (&d)[48], uint64_t descA, uint64_t descB, int scaleD) {
    asm volatile("{\n.reg .pred p;\n"
        "setp.ne.b32 p, %50, 0;\n"
        "wgmma.mma_async.sync.aligned.m64n96k16.f32.bf16.bf16 "
        "{%0,%1,%2,%3,%4,%5,%6,%7,%8,%9,%10,%11,%12,%13,%14,%15,%16,%17,%18,%19,%20,%21,%22,%23,%24,%25,%26,%27,%28,%29,%30,%31,%32,%33,%34,%35,%36,%37,%38,%39,%40,%41,%42,%43,%44,%45,%46,%47}, "
        "%48, %49, p, 1, 1, %51, %52;\n}\n"
        : "+f"(d[0]),"+f"(d[1]),"+f"(d[2]),"+f"(d[3]),"+f"(d[4]),"+f"(d[5]),"+f"(d[6]),"+f"(d[7]),"+f"(d[8]),"+f"(d[9]),"+f"(d[10]),"+f"(d[11]),"+f"(d[12]),"+f"(d[13]),"+f"(d[14]),"+f"(d[15]),"+f"(d[16]),"+f"(d[17]),"+f"(d[18]),"+f"(d[19]),"+f"(d[20]),"+f"(d[21]),"+f"(d[22]),"+f"(d[23]),"+f"(d[24]),"+f"(d[25]),"+f"(d[26]),"+f"(d[27]),"+f"(d[28]),"+f"(d[29]),"+f"(d[30]),"+f"(d[31]),"+f"(d[32]),"+f"(d[33]),"+f"(d[34]),"+f"(d[35]),"+f"(d[36]),"+f"(d[37]),"+f"(d[38]),"+f"(d[39]),"+f"(d[40]),"+f"(d[41]),"+f"(d[42]),"+f"(d[43]),"+f"(d[44]),"+f"(d[45]),"+f"(d[46]),"+f"(d[47])
        : "l"(descA), "l"(descB), "r"(scaleD), "n"(TA), "n"(TB));
}
constexpr int QK_PF = 2;
constexpr int QK_ST = 5;
constexpr int QK_A_BYTES = 128 * 512 * 2;
constexpr int QK_B_BYTES = 64 * 128 * 2;
constexpr int QK_STG = 2 * 64 * 64 * 2;
constexpr int QK_SMEM = QK_A_BYTES + QK_ST * QK_B_BYTES + QK_STG + 1024 + 256
;

__device__ __forceinline__ void unpack8(const uint4& v, float (&f)[8]) {
    const uint32_t u[4] = {v.x, v.y, v.z, v.w};
    #pragma unroll
    for (int i = 0; i < 4; i++) { f[2 * i] = __uint_as_float(u[i] << 16); f[2 * i + 1] = __uint_as_float(u[i] & 0xffff0000u); }
}
__device__ __forceinline__ float warp_sum(float v) {
    #pragma unroll
    for (int o = 16; o > 0; o >>= 1) v += __shfl_xor_sync(0xffffffffu, v, o);
    return v;
}
__device__ __forceinline__ uint4 lds128(uint32_t a) {
    uint4 v; asm volatile("ld.shared.v4.u32 {%0,%1,%2,%3}, [%4];" : "=r"(v.x), "=r"(v.y), "=r"(v.z), "=r"(v.w) : "r"(a)); return v;
}
__device__ __forceinline__ void sts128(uint32_t a, const uint4& v) {
    asm volatile("st.shared.v4.u32 [%0], {%1,%2,%3,%4};" :: "r"(a), "r"(v.x), "r"(v.y), "r"(v.z), "r"(v.w) : "memory");
}
__device__ __forceinline__ uint4 pack8(const float (&f)[8], float sc) {
    uint4 o;
    o.x = pack_bf16(f[0] * sc, f[1] * sc); o.y = pack_bf16(f[2] * sc, f[3] * sc);
    o.z = pack_bf16(f[4] * sc, f[5] * sc); o.w = pack_bf16(f[6] * sc, f[7] * sc);
    return o;
}

__device__ __forceinline__ void ln_rows_inplace(uint32_t sA, int row_base, int lane, uint32_t afull, int nbar, int aph) {
    const int row = row_base + (lane >> 1);
    const uint32_t rowa = sA + row * 128;
    uint32_t off[4];
    #pragma unroll
    for (int i = 0; i < 4; i++) off[i] = rowa + ((((lane & 1) * 4 + i) ^ (row & 7)) << 4);
    float sm0 = 0.f, sm1 = 0.f, sq0 = 0.f, sq1 = 0.f, shift = 0.f;
    #pragma unroll 1
    for (int c = 0; c < 8; c++) {
        if (c < nbar) mbar_wait(afull + 8 * c, aph);
        uint4 v[4];
        #pragma unroll
        for (int i = 0; i < 4; i++) v[i] = lds128(off[i] + c * 16384);
        if (c == 0) shift = __shfl_sync(0xffffffffu, __uint_as_float(v[0].x << 16), lane & ~1);
        #pragma unroll
        for (int i = 0; i < 4; i++) {
            float f[8]; unpack8(v[i], f);
            #pragma unroll
            for (int e = 0; e < 8; e += 2) {
                const float a = f[e] - shift, b = f[e + 1] - shift;
                sm0 += a; sm1 += b; sq0 = fmaf(a, a, sq0); sq1 = fmaf(b, b, sq1);
            }
        }
    }
    float sm = sm0 + sm1, sq = sq0 + sq1;
    sm += __shfl_xor_sync(0xffffffffu, sm, 1); sq += __shfl_xor_sync(0xffffffffu, sq, 1);
    const float dm = sm * (1.f / DM);
    const float var = fmaxf(sq * (1.f / DM) - dm * dm, 0.f);
    const float rs = rsqrtf(var + LN_EPS), nb = -(dm + shift) * rs;
    #pragma unroll 2
    for (int c = 0; c < 8; c++) {
        uint4 v[4];
        #pragma unroll
        for (int i = 0; i < 4; i++) v[i] = lds128(off[i] + c * 16384);
        #pragma unroll
        for (int i = 0; i < 4; i++) {
            float f[8]; unpack8(v[i], f);
            uint4 o;
            o.x = pack_bf16(fmaf(f[0], rs, nb), fmaf(f[1], rs, nb)); o.y = pack_bf16(fmaf(f[2], rs, nb), fmaf(f[3], rs, nb));
            o.z = pack_bf16(fmaf(f[4], rs, nb), fmaf(f[5], rs, nb)); o.w = pack_bf16(fmaf(f[6], rs, nb), fmaf(f[7], rs, nb));
            sts128(off[i] + c * 16384, o);
        }
    }
}

__device__ __forceinline__ int qkv_tile_count(int g) { return g < 2 ? 11 : (g == 2 ? 10 : (g < 7 ? 13 : 12)); }
__device__ __forceinline__ int qkv_tile_id(int g, int i) {
    if (g < 3) return 31 - (3 * i + g);
    const int idx = 5 * i + (g - 3);
    return 32 * (1 + (idx & 1)) + 31 - (idx >> 1);
}
struct QkvCtx {
    uint32_t sA, sBst, sStg, full, empty, sfull, sempty;
    int s, ph;
    int sph;
    int w, wq, lane;
    float osc;
};

__device__ __forceinline__ void qkv_epi_slice(const float (&acc)[64], int j2, uint32_t stg_row, int lane, float sc) {
    const int j = 2 * j2;
    const int cg = (j & 7) + (lane >> 4);
    stmatrix_x4(stg_row + ((cg ^ (lane & 7)) << 4),
                pack_bf16(acc[4 * j] * sc, acc[4 * j + 1] * sc), pack_bf16(acc[4 * j + 2] * sc, acc[4 * j + 3] * sc),
                pack_bf16(acc[4 * j + 4] * sc, acc[4 * j + 5] * sc), pack_bf16(acc[4 * j + 6] * sc, acc[4 * j + 7] * sc));
}
__device__ __forceinline__ void qkv_stg_acquire(QkvCtx& c) { mbar_wait(c.sempty + 8 * c.w, c.sph ^ 1); }
__device__ __forceinline__ void qkv_stg_publish(QkvCtx& c) {
    __syncwarp();
    if (c.lane == 0) mbar_arrive(c.sfull + 8 * c.w);
    c.sph ^= 1;
}
__device__ __forceinline__ void qkv_release(const QkvCtx& c, int stage) {
    if (c.wq < 2 && c.lane == 0) mbar_arrive_cta(c.empty + 8 * stage, c.wq);
}

#define PROF_SKIP 0
#define QTS()
template<bool WAIT_A, bool HAS_PREV, int W>
__device__ __forceinline__ void qkv_tile(QkvCtx& c, float (&cur)[64], float (&prev)[64], uint32_t afull, int aph) {
    const uint64_t dA = make_desc(c.sA + c.w * 8192, 16, 1024);
    const int r = (c.lane & 7) + ((c.lane >> 3) & 1) * 8;
    const uint32_t stg_row = c.sStg + c.w * 8192 + (c.wq * 16 + r) * 128;
    #pragma unroll
    for (int kb = 0; kb < 8; kb++) {
        QTS();
        if (WAIT_A) mbar_wait(afull + 8 * kb, aph);
        mbar_wait(c.full + 8 * c.s, c.ph);
        if (WAIT_A && kb == 0) { TL_FIRST(0); }
        QTS();
        const uint64_t dB = make_desc(c.sBst + c.s * QK_B_BYTES, 8192, 1024);
        wgmma_fence();
        #pragma unroll
        for (int k = 0; k < 4; k++)
            wgmma_ss_n128<0, 1>(cur, desc_add(dA, kb * 16384 + k * 32), desc_add(dB, k * 2048), (kb | k) != 0);
        wgmma_commit();
        const int scur = c.s;
        const int sprev = c.s == 0 ? QK_ST - 1 : c.s - 1;
        if (++c.s == QK_ST) { c.s = 0; c.ph ^= 1; }
        QTS();
        if (kb > 0) { wgmma_wait<1>(); qkv_release(c, sprev); }
        QTS();
        if (HAS_PREV) {
            const int e = kb - 2 * W;
            if (e == 0 || e == 4) qkv_stg_acquire(c);
            if (e == 0 || e == 1 || e == 4 || e == 5) {
                const int j2 = (e >> 2) * 4 + (e & 1) * 2;
                qkv_epi_slice(prev, j2, stg_row, c.lane, c.osc); qkv_epi_slice(prev, j2 + 1, stg_row, c.lane, c.osc);
            }
            if (e == 1 || e == 5) qkv_stg_publish(c);
        }
        if (kb == 7) {
            wgmma_wait<0>();
            fence_regs(cur);
            qkv_release(c, scur);
        }
    }
}
__device__ __forceinline__ void qkv_drain(QkvCtx& c, float (&acc)[64]) {
    const int r = (c.lane & 7) + ((c.lane >> 3) & 1) * 8;
    const uint32_t stg_row = c.sStg + c.w * 8192 + (c.wq * 16 + r) * 128;
    #pragma unroll
    for (int h = 0; h < 2; h++) {
        qkv_stg_acquire(c);
        #pragma unroll
        for (int j = 0; j < 4; j++) qkv_epi_slice(acc, 4 * h + j, stg_row, c.lane, c.osc);
        qkv_stg_publish(c);
    }
}

__global__ void __cluster_dims__(2, 1, 1) __launch_bounds__(384, 1)
k_qkv(const __grid_constant__ CUtensorMap mX, const __grid_constant__ CUtensorMap mC,
      const __grid_constant__ CUtensorMap mWq, const __grid_constant__ CUtensorMap mWk,
      const __grid_constant__ CUtensorMap mWv, const __grid_constant__ CUtensorMap mOut,
      const bf16* __restrict__ x, bf16* __restrict__ hacc,
      const bf16* __restrict__ wq, const bf16* __restrict__ wk, const bf16* __restrict__ wv) {
    TL_START(0);
#define TS2()
    TS2();
    extern __shared__ uint8_t smem_raw[];
    const uint32_t sA = (smem_u32(smem_raw) + 1023) & ~1023u;
    const uint32_t sBst = sA + QK_A_BYTES, sStg = sBst + QK_ST * QK_B_BYTES, sB = sStg + QK_STG;
    const uint32_t full = sB, empty = full + 8 * QK_ST, afull = empty + 8 * QK_ST,
                   sfull = afull + 64, sempty = sfull + 16;
    const int warp = __shfl_sync(0xffffffffu, threadIdx.x >> 5, 0);
    const int lane = threadIdx.x & 31;
    const uint32_t rank = cluster_ctarank();
    const int cl = blockIdx.x >> 1;
    const int rowblk = (cl >> 3) * 2 + rank;
    const int g = cl & 7;
    const int ntile = qkv_tile_count(g);
    if (warp == 0 && elect_one()) {
        for (int i = 0; i < QK_ST; i++) { mbar_init(full + 8 * i, 1); mbar_init(empty + 8 * i, 4); }
        for (int i = 0; i < 8; i++) mbar_init(afull + 8 * i, 1);
        for (int i = 0; i < 2; i++) { mbar_init(sfull + 8 * i, 4); mbar_init(sempty + 8 * i, 1); }
        fence_mbar_init();
        fence_proxy_async();
        const CUtensorMap* mA = (g < 3) ? &mX : &mC;
        const int n_early = (g < 3) ? 8 : 2;
        for (int kb = 0; kb < n_early; kb++) {
            mbar_expect_tx(afull + 8 * kb, 16384);
            tma_load_2d(sA + kb * 16384, mA, afull + 8 * kb, kb * 64, rowblk * 128);
        }
    }
    __syncthreads();
    TS2();
    asm volatile("barrier.cluster.arrive.relaxed.aligned;" ::: "memory");
    cluster_wait();
    pdl_launch();
    TS2();

    if (warp < 4) {
        reg_dealloc<40>();
        if (warp == 0) {
            if (elect_one()) {
                int s = 0, ph = 1;
                for (int i = 0; i < ntile; i++) {
                    const int n = qkv_tile_id(g, i);
                    const CUtensorMap* mW = n < 32 ? &mWq : (n < 64 ? &mWk : &mWv);
                    const int col = (n & 31) * 128 + rank * 64;
                    for (int kb = 0; kb < 8; kb++) {
                        mbar_wait(empty + 8 * s, ph);
                        mbar_expect_tx(full + 8 * s, QK_B_BYTES);
                        tma_load_2d_mc(sBst + s * QK_B_BYTES + rank * 8192, mW, full + 8 * s, col, kb * 64, (uint16_t)3);
                        if (++s == QK_ST) { s = 0; ph ^= 1; }
                        if (i == 0 && g >= 3 && kb < 6) {
                            mbar_expect_tx(afull + 8 * (kb + 2), 16384);
                            tma_load_2d(sA + (kb + 2) * 16384, &mC, afull + 8 * (kb + 2), (kb + 2) * 64, rowblk * 128);
                        }
                    }
                }
                for (int i = 0; i < QK_ST; i++) { mbar_wait(empty + 8 * s, ph); if (++s == QK_ST) { s = 0; ph ^= 1; } }
            }
        } else if (warp < 3) {
            const int w = warp - 1;
            const bool leader = elect_one();
            for (int i = 0; i < 2 * ntile; i++) {
                if (leader) {
                    mbar_wait(sfull + 8 * w, i & 1);
                    fence_proxy_async();
                    tma_store_2d(&mOut, sStg + w * 8192, (i & 1) * 64, qkv_tile_id(g, i >> 1) * S_LEN + rowblk * 128 + w * 64);
                    tma_commit();
                }
                __syncwarp();
                const int ip = (i >> 1) + QK_PF + 1;
                if ((i & 1) == 0 && ip < ntile) {
                    const int np = qkv_tile_id(g, ip);
                    prefetch_l2((np < 32 ? wq : (np < 64 ? wk : wv)) + (size_t)((cl >> 3) * 64 + w * 32 + lane) * (NH * HD) + (np & 31) * 128 + rank * 64);
                }
                if (leader) {
                    tma_wait_read<0>();
                    mbar_arrive(sempty + 8 * w);
                }
            }
            if (leader) { tma_wait<0>(); TL_END(0); }
        } else {
            mbar_wait(afull + 8 * 7, 0);
            for (int i = 1; i < QK_PF + 1; i++) {
                const int np = qkv_tile_id(g, i);
                const bf16* wp = (np < 32 ? wq : (np < 64 ? wk : wv)) + (size_t)((cl >> 3) * 64 + lane) * (NH * HD) + (np & 31) * 128 + rank * 64;
                prefetch_l2(wp); prefetch_l2(wp + 32 * (NH * HD));
            }
            const uint4* xs = reinterpret_cast<const uint4*>(x + (size_t)blockIdx.x * 16 * DM);
            uint4* hd = reinterpret_cast<uint4*>(hacc + (size_t)blockIdx.x * 16 * DM);
            #pragma unroll 4
            for (int i = lane; i < 16 * DM / 8; i += 32) hd[i] = __ldg(xs + i);
        }
    } else {
        reg_alloc<232>();
        QkvCtx c;
        c.sA = sA; c.sBst = sBst; c.sStg = sStg; c.full = full; c.empty = empty; c.sfull = sfull; c.sempty = sempty;
        c.s = 0; c.ph = 0; c.sph = 0; c.w = (warp >> 2) - 1; c.wq = warp & 3; c.lane = lane;
        c.osc = g < 3 ? AT_SCALE : 1.f;
        float acc0[64], acc1[64];
        if (g < 3) {
            TS2();
            ln_rows_inplace(sA, c.w * 64 + c.wq * 16, lane, afull, 8, 0);
            TS2();
            fence_proxy_async();
            bar_sync(3 + c.w, 128);
            TS2();
        }
        if (c.w == 0) {
            qkv_tile<true, false, 0>(c, acc0, acc1, afull, 0);
            int i = 1;
            for (; i + 1 < ntile; i += 2) {
                qkv_tile<false, true, 0>(c, acc1, acc0, afull, 0);
                qkv_tile<false, true, 0>(c, acc0, acc1, afull, 0);
            }
            if (i < ntile) { qkv_tile<false, true, 0>(c, acc1, acc0, afull, 0); qkv_drain(c, acc1); }
            else qkv_drain(c, acc0);
        } else {
            qkv_tile<true, false, 1>(c, acc0, acc1, afull, 0);
            int i = 1;
            for (; i + 1 < ntile; i += 2) {
                qkv_tile<false, true, 1>(c, acc1, acc0, afull, 0);
                qkv_tile<false, true, 1>(c, acc0, acc1, afull, 0);
            }
            if (i < ntile) { qkv_tile<false, true, 1>(c, acc1, acc0, afull, 0); qkv_drain(c, acc1); }
            else qkv_drain(c, acc0);
        }
        TS2();
    }
}
constexpr int AT_KST = 2, AT_VST = 2;
constexpr int AT_TILE = 128 * 128 * 2;
constexpr int AT_SMEM = (3 + AT_KST + AT_VST) * AT_TILE + 1024 + 256
;
constexpr float AT_BIG = 1073741824.f;
#define AT_PINGPONG 1

struct PrefetchList { const void* ptr[5]; uint32_t bytes[5]; float* colsum; const bf16* qkv; };
#define AT_PFD 2
#define AT_WPF 10

struct AttnSched { ulonglong2 e[160]; };
#define attn_get_tile(t, head, qt) attn_get_tile_(my_list, (t), (head), (qt))
__device__ __forceinline__ bool attn_get_tile_(const ulonglong2& list, int t, int& head, int& qt) {
    if (t >= (int)(list.y >> 48)) return false;
    const int e = (int)((t < 4 ? list.x >> (16 * t) : list.y >> (16 * (t - 4))) & 0xffff);
    head = e >> 4; qt = e & 15;
    return true;
}

__device__ __forceinline__ void attn_qk(float (&S)[64], uint64_t dq, uint64_t dk) {
    #pragma unroll
    for (int k = 0; k < 8; k++) {
        const uint32_t off = (k >> 2) * 16384 + (k & 3) * 32;
        wgmma_ss_n128<0, 0>(S, desc_add(dq, off), desc_add(dk, off), k > 0);
    }
}
__device__ __forceinline__ void attn_pv(float (&O)[64], uint32_t (&P)[32], uint64_t dv, int acc) {
    #pragma unroll
    for (int k = 0; k < 8; k++)
        wgmma_rs_n128<1>(O, P[4 * k], P[4 * k + 1], P[4 * k + 2], P[4 * k + 3], desc_add(dv, k * 2048), k > 0 ? 1 : acc);
}
__device__ __forceinline__ float quad_max(float v) {
    v = fmaxf(v, __shfl_xor_sync(0xffffffffu, v, 1));
    return fmaxf(v, __shfl_xor_sync(0xffffffffu, v, 2));
}
__device__ __forceinline__ float quad_sum(float v) {
    v += __shfl_xor_sync(0xffffffffu, v, 1);
    return v + __shfl_xor_sync(0xffffffffu, v, 2);
}
__device__ __forceinline__ void attn_rowmax(const float (&S)[64], float& mx0, float& mx1) {
    float a0 = fmaxf(S[0], S[1]), a1 = fmaxf(S[2], S[3]), b0 = fmaxf(S[4], S[5]), b1 = fmaxf(S[6], S[7]);
    #pragma unroll
    for (int j = 2; j < 16; j += 2) {
        a0 = fmaxf(a0, fmaxf(S[4 * j], S[4 * j + 1]));
        a1 = fmaxf(a1, fmaxf(S[4 * j + 2], S[4 * j + 3]));
        b0 = fmaxf(b0, fmaxf(S[4 * j + 4], S[4 * j + 5]));
        b1 = fmaxf(b1, fmaxf(S[4 * j + 6], S[4 * j + 7]));
    }
    mx0 = quad_max(fmaxf(a0, b0));
    mx1 = quad_max(fmaxf(a1, b1));
}
__device__ __forceinline__ bool attn_first_max(const float (&S)[64], float& m0, float& m1) {
    attn_rowmax(S, m0, m1);
    const bool zero = __all_sync(0xffffffffu, fabsf(m0) <= 16.f && fabsf(m1) <= 16.f);
    if (zero) { m0 = 0.f; m1 = 0.f; }
    return zero;
}
template<bool ZERO>
__device__ __forceinline__ void attn_exp_pack_(float (&S)[64], float m0, float m1, uint32_t (&P)[32], float& s0, float& s1) {
    float a0 = 0.f, a1 = 0.f, b0 = 0.f, b1 = 0.f;
    #pragma unroll
    for (int j = 0; j < 16; j++) {
        if (!ZERO) { S[4 * j] -= m0; S[4 * j + 1] -= m0; S[4 * j + 2] -= m1; S[4 * j + 3] -= m1; }
        const float e0 = ex2(S[4 * j]), e1 = ex2(S[4 * j + 1]), e2 = ex2(S[4 * j + 2]), e3 = ex2(S[4 * j + 3]);
        a0 += e0; b0 += e1; a1 += e2; b1 += e3;
        P[2 * j] = pack_bf16(e0, e1); P[2 * j + 1] = pack_bf16(e2, e3);
    }
    s0 = a0 + b0; s1 = a1 + b1;
}
__device__ __forceinline__ void attn_exp_pack(float (&S)[64], float m0, float m1, bool zero, uint32_t (&P)[32], float& s0, float& s1) {
    if (zero) attn_exp_pack_<true>(S, m0, m1, P, s0, s1); else attn_exp_pack_<false>(S, m0, m1, P, s0, s1);
}
__device__ __forceinline__ void attn_exp_pack_shift(const float (&S)[64], float d0, float d1, uint32_t (&P)[32], float& s0, float& s1) {
    float a0 = 0.f, a1 = 0.f, b0 = 0.f, b1 = 0.f;
    #pragma unroll
    for (int j = 0; j < 16; j++) {
        const float e0 = ex2(S[4 * j] - d0), e1 = ex2(S[4 * j + 1] - d0), e2 = ex2(S[4 * j + 2] - d1), e3 = ex2(S[4 * j + 3] - d1);
        a0 += e0; b0 += e1; a1 += e2; b1 += e3;
        P[2 * j] = pack_bf16(e0, e1); P[2 * j + 1] = pack_bf16(e2, e3);
    }
    s0 = a0 + b0; s1 = a1 + b1;
}
__global__ void __launch_bounds__(384, 1)
k_attn(const __grid_constant__ CUtensorMap mQKV, const __grid_constant__ CUtensorMap mCtx, const PrefetchList pf,
       const __grid_constant__ AttnSched sched) {
    TL_START(1);
#define TS6()
    TS6();
    ulonglong2 my_list = sched.e[blockIdx.x];
    asm volatile("" : "+l"(my_list.x), "+l"(my_list.y));
    extern __shared__ uint8_t smem_raw[];
    const uint32_t sQ = (smem_u32(smem_raw) + 1023) & ~1023u;
    const uint32_t sK = sQ + 2 * AT_TILE, sV = sK + AT_KST * AT_TILE, sO = sV + AT_VST * AT_TILE, sB = sO + AT_TILE;
    const uint32_t qfull = sB, qempty = sB + 16, kfull = sB + 32, kempty = kfull + 8 * AT_KST,
                   vfull = kempty + 8 * AT_KST, vempty = vfull + 8 * AT_VST, ofull = vempty + 8 * AT_VST, oempty = ofull + 16, stepctr = oempty + 16;
    const int warp = __shfl_sync(0xffffffffu, threadIdx.x >> 5, 0);
    const int lane = threadIdx.x & 31;
    if (threadIdx.x == 0) {
        for (int i = 0; i < 2; i++) { mbar_init(qfull + 8 * i, 1); mbar_init(qempty + 8 * i, 2); mbar_init(ofull + 8 * i, 4); mbar_init(oempty + 8 * i, 1); }
        for (int i = 0; i < AT_KST; i++) { mbar_init(kfull + 8 * i, 1); mbar_init(kempty + 8 * i, 2); }
        for (int i = 0; i < AT_VST; i++) { mbar_init(vfull + 8 * i, 1); mbar_init(vempty + 8 * i, 2); }
        asm volatile("st.shared.u32 [%0], %1;" :: "r"(stepctr), "r"(0) : "memory");
        fence_mbar_init();
        prefetch_tmap(&mQKV); prefetch_tmap(&mCtx);
    }
    __syncthreads();
    TS6();
    pdl_launch();
    pdl_wait();
    TS6();
    if (threadIdx.x == 0) { TL_MARK(1); }

    if (warp < 4) {
        reg_dealloc<40>();
        if (warp == 0) {
          if (elect_one()) {
            int ks = 0, kph = 1, vs = 0, vph = 1;
            int head, qt;
            bool have = attn_get_tile(0, head, qt);
            if (have) {
                mbar_expect_tx(qfull, AT_TILE);
                tma_load_3d(sQ, &mQKV, qfull, 0, head * S_LEN + qt * 128, 0);
            }
            for (int t = 0; have; t++) {
                const int krow = (NH + head) * S_LEN, vrow = (2 * NH + head) * S_LEN;
                for (int j = 0; j <= qt + 1; j++) {
                    if (j <= qt) {
                        mbar_wait(kempty + 8 * ks, kph);
                        mbar_expect_tx(kfull + 8 * ks, AT_TILE);
                        tma_load_3d(sK + ks * AT_TILE, &mQKV, kfull + 8 * ks, 0, krow + j * 128, 0);
                        if (++ks == AT_KST) { ks = 0; kph ^= 1; }
                    }
                    if (j > 0) {
                        mbar_wait(vempty + 8 * vs, vph);
                        mbar_expect_tx(vfull + 8 * vs, AT_TILE);
                        tma_load_3d(sV + vs * AT_TILE, &mQKV, vfull + 8 * vs, 0, vrow + (j - 1) * 128, 0);
                        if (++vs == AT_VST) { vs = 0; vph ^= 1; }
                    }
                }
                have = attn_get_tile(t + 1, head, qt);
                if (have) {
                    const int b = (t + 1) & 1, u = (t + 1) >> 1;
                    mbar_wait(qempty + 8 * b, (u & 1) ^ 1);
                    mbar_expect_tx(qfull + 8 * b, AT_TILE);
                    tma_load_3d(sQ + b * AT_TILE, &mQKV, qfull + 8 * b, 0, head * S_LEN + qt * 128, 0);
                }
            }
          }
        } else if (warp == 1) {
            if (elect_one()) {
                int head, qt;
                for (int t = 0; attn_get_tile(t, head, qt); t++) {
                    #pragma unroll
                    for (int w = 0; w < 2; w++) {
                        mbar_wait(ofull + 8 * w, t & 1);
                        fence_proxy_async();
                        const uint32_t src = sO + w * 16384;
                        tma_store_2d(&mCtx, src, head * 128, qt * 128 + w * 64);
                        tma_store_2d(&mCtx, src + 8192, head * 128 + 64, qt * 128 + w * 64);
                        tma_commit();
                    }
                    tma_wait_read<1>(); mbar_arrive(oempty);
                    tma_wait_read<0>(); mbar_arrive(oempty + 8);
                }
                tma_wait<0>();
                TL_END(1);
            }
        } else if (warp == 2) {
            for (int c0 = blockIdx.x * 8; c0 < DM + FF; c0 += gridDim.x * 8) {
                const bool first = c0 < DM;
                const bf16* wp = first ? static_cast<const bf16*>(pf.ptr[1]) + c0 : static_cast<const bf16*>(pf.ptr[3]) + (c0 - DM);
                const int ld = first ? DM : FF;
                float a[8] = {0.f, 0.f, 0.f, 0.f, 0.f, 0.f, 0.f, 0.f};
                #pragma unroll 2
                for (int r = lane; r < DM; r += 32) {
                    float f[8]; unpack8(__ldg(reinterpret_cast<const uint4*>(wp + (size_t)r * ld)), f);
                    #pragma unroll
                    for (int e = 0; e < 8; e++) a[e] += f[e];
                }
                #pragma unroll
                for (int e = 0; e < 8; e++) a[e] = warp_sum(a[e]);
                if (lane == 0) {
                    *reinterpret_cast<float4*>(pf.colsum + c0) = make_float4(a[0], a[1], a[2], a[3]);
                    *reinterpret_cast<float4*>(pf.colsum + c0 + 4) = make_float4(a[4], a[5], a[6], a[7]);
                }
            }
            int head, qt, tp = 0, jp = 0, ahead = 0, wstep = -AT_WPF;
            for (int t = 0; attn_get_tile(t, head, qt); t++) wstep += qt + 1;
            bool have = attn_get_tile(0, head, qt);
            auto next_blk = [&]() { if (++jp > qt) { jp = 0; tp++; have = attn_get_tile(tp, head, qt); } };
            while (have && ahead < AT_PFD) { next_blk(); ahead++; }
            for (int st = 0; have; st++) {
                uint32_t cur, spins = 0;
                do {
                    asm volatile("ld.volatile.shared.u32 %0, [%1];" : "=r"(cur) : "r"(stepctr));
                    if ((int)cur >= st) break;
                    __nanosleep(200);
                } while (++spins < 100000u);
                if (tp >= 2) {
                    if (jp == 0) {
                        const bf16* qp = pf.qkv + ((size_t)head * S_LEN + qt * 128) * HD;
                        #pragma unroll
                        for (int r = 0; r < 8; r++) prefetch_l2(qp + (r * 32 + lane) * 64);
                    }
                    if (qt == 15) {
                        const bf16* kp = pf.qkv + ((size_t)(NH + head) * S_LEN + jp * 128) * HD;
                        const bf16* vp = pf.qkv + ((size_t)(2 * NH + head) * S_LEN + jp * 128) * HD;
                        #pragma unroll
                        for (int r = 0; r < 8; r++) { prefetch_l2(kp + (r * 32 + lane) * 64); prefetch_l2(vp + (r * 32 + lane) * 64); }
                    }
                }
                if (st == wstep) {
                    #pragma unroll 1
                    for (int k = 0; k < 5; k++) {
                        const char* base = reinterpret_cast<const char*>(pf.ptr[k]);
                        for (uint32_t o = (blockIdx.x * 32 + lane) * 128u; o < pf.bytes[k]; o += gridDim.x * 32 * 128u) prefetch_l2(base + o);
                    }
                }
                next_blk();
            }
        } else if (warp == 3) {
            int ks = 0, kph = 0, vs = 0, vph = 0, nstep = 0;
            int head, qt;
            bool have = attn_get_tile(0, head, qt);
            for (int t = 0; have; t++) {
                int nh, nq;
                const bool nxt = attn_get_tile(t + 1, nh, nq);
                const int j0 = (t == 0) ? 0 : 1;
                for (int j = j0; j <= qt + 1; j++) {
                    const bool last = j == qt + 1;
                    if (j == 0) mbar_wait(qfull, 0);
                    if (last && nxt) mbar_wait(qfull + 8 * ((t + 1) & 1), ((t + 1) >> 1) & 1);
                    if (!last || nxt) { mbar_wait(kfull + 8 * ks, kph); if (++ks == AT_KST) { ks = 0; kph ^= 1; } }
                    if (j > 0) { mbar_wait(vfull + 8 * vs, vph); if (++vs == AT_VST) { vs = 0; vph ^= 1; } }
                    bar_sync(1, 288);
                    if (lane == 0) asm volatile("st.volatile.shared.u32 [%0], %1;" :: "r"(stepctr), "r"(++nstep) : "memory");
                    bar_sync(2, 288);
                }
                have = nxt; qt = nq; head = nh;
            }
        }
    } else {
        reg_alloc<232>();
        const int w = (warp >> 2) - 1;
        const int wq = warp & 3;
        const int row0 = w * 64 + wq * 16 + (lane >> 2);
        const int qc = (lane & 3) * 2;
        if (w == 1) bar_arrive(1, 288);
#define ATS()
        float O[64], S[64];
        uint32_t P0[32], P1[32];
        int ks = 0, vs = 0;
        int head, qt;
        float m0 = 0.f, m1 = 0.f, l0 = 0.f, l1 = 0.f;
        bool zm = false;
        const int thr0 = row0 - qc;

        auto mask_diag = [&]() {
            int thr = thr0;
            asm volatile("" : "+r"(thr));
            #pragma unroll
            for (int j = 0; j < 16; j++) {
                if (8 * j > thr) S[4 * j] = -INFINITY;
                if (8 * j + 1 > thr) S[4 * j + 1] = -INFINITY;
                if (8 * j - 8 > thr) S[4 * j + 2] = -INFINITY;
                if (8 * j - 7 > thr) S[4 * j + 3] = -INFINITY;
            }
        };
        auto epilogue = [&](int t, float i0, float i1) {
            const int r = (lane & 7) + ((lane >> 3) & 1) * 8;
            const uint32_t rowaddr = sO + w * 16384 + (wq * 16 + r) * 128;
            mbar_wait(oempty + 8 * w, (t & 1) ^ 1);
            #pragma unroll
            for (int j = 0; j < 16; j += 2) {
                const int cg = j + (lane >> 4);
                const uint32_t a = rowaddr + (cg >> 3) * 8192 + (((cg & 7) ^ (lane & 7)) << 4);
                stmatrix_x4(a, pack_bf16(O[4 * j] * i0, O[4 * j + 1] * i0), pack_bf16(O[4 * j + 2] * i1, O[4 * j + 3] * i1),
                               pack_bf16(O[4 * j + 4] * i0, O[4 * j + 5] * i0), pack_bf16(O[4 * j + 6] * i1, O[4 * j + 7] * i1));
            }
            __syncwarp();
            if (lane == 0) mbar_arrive(ofull + 8 * w);
        };
        const uint32_t sig = (wq == 0 && lane == 0);
        int t = 0, j = 1;
        int nhead = 0, nqt = 0;
        bool have_next = false;
        auto step = [&](uint32_t (&Pin)[32], uint32_t (&Pout)[32]) {
            const bool trans = j > qt;
            const int qb = (t + (trans ? 1 : 0)) & 1;
            ATS();
            bar_sync(1 + w, 288);
            ATS();
            wgmma_fence();
            attn_qk(S, make_desc(sQ + qb * AT_TILE + w * 8192, 16, 1024), make_desc(sK + ks * AT_TILE, 16, 1024));
            wgmma_commit();
            attn_pv(O, Pin, make_desc(sV + vs * AT_TILE, 16384, 1024), j != 1);
            wgmma_commit();
            bar_arrive(1 + (w ^ 1), 288);
            ATS();
            wgmma_wait<1>();
            fence_regs(S);
            ATS();
            const bool diag = trans ? (nqt == 0) : (j == qt);
            mbar_arrive_if(kempty + 8 * ks, sig);
            mbar_arrive_if(qempty + 8 * qb, sig && diag);
            ks ^= 1;
            if (__builtin_expect(diag, 0)) mask_diag();
            float lp0 = l0, lp1 = l1;
            if (__builtin_expect(trans, 0)) {
                zm = attn_first_max(S, m0, m1);
                l0 = 0.f; l1 = 0.f;
            }
            ATS();
            float s0, s1;
            attn_exp_pack(S, m0, m1, zm, Pout, s0, s1);
            const bool bad = __any_sync(0xffffffffu, !(s0 <= AT_BIG && s1 <= AT_BIG));
            ATS();
            if (__builtin_expect(bad, 0)) {
                asm volatile("wgmma.wait_group.sync.aligned 0; // fallback" ::: "memory");
                fence_regs(O);
                float d0, d1;
                attn_rowmax(S, d0, d1);
                d0 = fmaxf(d0, 0.f); d1 = fmaxf(d1, 0.f);
                m0 += d0; m1 += d1; zm = false;
                if (!trans) {
                    const float sc0 = ex2(-d0), sc1 = ex2(-d1);
                    l0 *= sc0; l1 *= sc1;
                    #pragma unroll
                    for (int i = 0; i < 16; i++) {
                        O[4 * i] *= sc0; O[4 * i + 1] *= sc0; O[4 * i + 2] *= sc1; O[4 * i + 3] *= sc1;
                    }
                }
                attn_exp_pack_shift(S, d0, d1, Pout, s0, s1);
            } else {
                asm volatile("wgmma.wait_group.sync.aligned 0; // common" ::: "memory");
            }
            fence_regs(O); fence_regs(Pin);
            mbar_arrive_if(vempty + 8 * vs, sig);
            vs ^= 1;
            l0 += s0; l1 += s1;
            if (__builtin_expect(trans, 0)) {
                epilogue(t, __fdividef(1.f, quad_sum(lp0)), __fdividef(1.f, quad_sum(lp1)));
                t++; head = nhead; qt = nqt; j = 1;
                have_next = attn_get_tile(t + 1, nhead, nqt);
            } else j++;
            ATS();
        };

        auto final_pv = [&](uint32_t (&Pin)[32]) {
            bar_sync(1 + w, 288);
            wgmma_fence();
            attn_pv(O, Pin, make_desc(sV + vs * AT_TILE, 16384, 1024), j != 1);
            wgmma_commit();
            bar_arrive(1 + (w ^ 1), 288);
            const float i0 = __fdividef(1.f, quad_sum(l0)), i1 = __fdividef(1.f, quad_sum(l1));
            wgmma_wait<0>();
            fence_regs(O); fence_regs(Pin);
            epilogue(t, i0, i1);
        };

        if (attn_get_tile(0, head, qt)) {
            have_next = attn_get_tile(1, nhead, nqt);
            TS6();
            bar_sync(1 + w, 288);
            TL_FIRST(1);
            TS6();
            wgmma_fence();
            attn_qk(S, make_desc(sQ + w * 8192, 16, 1024), make_desc(sK + ks * AT_TILE, 16, 1024));
            wgmma_commit();
            bar_arrive(1 + (w ^ 1), 288);
            wgmma_wait<0>();
            fence_regs(S);
            mbar_arrive_if(kempty + 8 * ks, sig);
            mbar_arrive_if(qempty, sig && qt == 0);
            ks ^= 1;
            TS6();
            if (qt == 0) mask_diag();
            zm = attn_first_max(S, m0, m1);
            attn_exp_pack(S, m0, m1, zm, P0, l0, l1);
            TS6();
            while (true) {
                if (j > qt && !have_next) { final_pv(P0); break; }
                step(P0, P1);
                if (j > qt && !have_next) { final_pv(P1); break; }
                step(P1, P0);
            }
        }
    }
}
__device__ __forceinline__ float gelu_tanh(float x) {
    const float u = x * fmaf(x * x, 0.044715f * 0.7978845608028654f, 0.7978845608028654f);
    float t;
    asm("tanh.approx.f32 %0, %1;" : "=f"(t) : "f"(u));
    const float hx = 0.5f * x;
    return fmaf(hx, t, hx);
}
__device__ __forceinline__ float gelu_half(float h) {
    const float u = h * fmaf(h * h, 8.f * 0.044715f * 0.7978845608028654f, 2.f * 0.7978845608028654f);
    float t;
    asm("tanh.approx.f32 %0, %1;" : "=f"(t) : "f"(u));
    return fmaf(h, t, h);
}
__device__ __forceinline__ float bf_lo(uint32_t u) { return __uint_as_float(u << 16); }
__device__ __forceinline__ float bf_hi(uint32_t u) { return __uint_as_float(u & 0xffff0000u); }
__device__ __forceinline__ void cluster_sync_relaxed() {
    asm volatile("barrier.cluster.arrive.relaxed.aligned;" ::: "memory");
    cluster_wait();
}

constexpr int GO_ST = 4;
constexpr int GO_STAGE = 16384 + 32768;
constexpr int GO_SMEM = GO_ST * GO_STAGE + 32768 + 1024 + 256;

__global__ void __cluster_dims__(2, 1, 1) __launch_bounds__(384, 1)
k_oproj(const __grid_constant__ CUtensorMap mCtx, const __grid_constant__ CUtensorMap mWo, const __grid_constant__ CUtensorMap mH) {
    TL_START(2);
    GTS_DECL
    GTS();
    extern __shared__ uint8_t smem_raw[];
    const uint32_t s0 = (smem_u32(smem_raw) + 1023) & ~1023u;
    const uint32_t sStg = s0 + GO_ST * GO_STAGE, full = sStg + 32768, empty = full + 8 * GO_ST;
    const int warp = __shfl_sync(0xffffffffu, threadIdx.x >> 5, 0);
    const int lane = threadIdx.x & 31;
    const uint32_t rank = cluster_ctarank();
    const int cl = blockIdx.x >> 1;
    const int rowblk = (cl >> 3) * 2 + rank, nh = cl & 1, ks = (cl >> 1) & 3;
    if (warp == 0 && elect_one()) {
        for (int i = 0; i < GO_ST; i++) { mbar_init(full + 8 * i, 1); mbar_init(empty + 8 * i, 4); }
        fence_mbar_init();
        fence_proxy_async();
        prefetch_tmap(&mCtx); prefetch_tmap(&mWo); prefetch_tmap(&mH);
    }
    __syncthreads();
    cluster_sync_relaxed();
    pdl_launch();
    if (warp < 4) {
        reg_dealloc<40>();
        if (warp == 0 && elect_one()) {
            for (int kb = 0; kb < GO_ST; kb++) {
                mbar_expect_tx(full + 8 * kb, GO_STAGE);
                tma_load_3d_mc(s0 + kb * GO_STAGE + 16384 + rank * 16384, &mWo, full + 8 * kb, 0, ks * 1024 + kb * 64, nh * 4 + rank * 2, (uint16_t)3);
            }
            pdl_wait();
            if (true) { TL_MARK(2); }
            int s = 0, ph = 1;
            for (int kb = 0; kb < 16; kb++) {
                const int k0 = ks * 1024 + kb * 64;
                const uint32_t st = s0 + s * GO_STAGE;
                if (kb >= GO_ST) {
                    mbar_wait(empty + 8 * s, ph);
                    mbar_expect_tx(full + 8 * s, GO_STAGE);
                    tma_load_3d_mc(st + 16384 + rank * 16384, &mWo, full + 8 * s, 0, k0, nh * 4 + rank * 2, (uint16_t)3);
                }
                tma_load_2d(st, &mCtx, full + 8 * s, k0, rowblk * 128);
                if (++s == GO_ST) { s = 0; ph ^= 1; }
            }
            for (int i = 0; i < GO_ST; i++) { mbar_wait(empty + 8 * s, ph); if (++s == GO_ST) { s = 0; ph ^= 1; } }
        }
    } else {
        reg_alloc<232>();
        const int w = (warp >> 2) - 1, wq = warp & 3;
        float accL[64], accH[64];
        int s = 0, ph = 0;
        for (int kb = 0; kb < 16 - GO_ST; kb++) {
            mbar_wait(full + 8 * s, ph);
            if (kb == 0) { TL_FIRST(2); }
            if (kb == 0 || kb == 8) GTS();
            const uint32_t st = s0 + s * GO_STAGE;
            const uint64_t dA = make_desc(st + w * 8192, 16, 1024), dB = make_desc(st + 16384, 8192, 1024);
            wgmma_fence();
            #pragma unroll
            for (int k = 0; k < 4; k++) {
                wgmma_ss_n128<0, 1>(accL, desc_add(dA, k * 32), desc_add(dB, k * 2048), (kb | k) != 0);
                wgmma_ss_n128<0, 1>(accH, desc_add(dA, k * 32), desc_add(dB, 16384 + k * 2048), (kb | k) != 0);
            }
            wgmma_commit();
            wgmma_wait<1>();
            if (kb > 0) { const int sp = s == 0 ? GO_ST - 1 : s - 1; if (wq < 2 && lane == 0) mbar_arrive_cta(empty + 8 * sp, wq); }
            if (++s == GO_ST) { s = 0; ph ^= 1; }
        }
        {
            int s2 = s, ph2 = ph;
            #pragma unroll
            for (int i = 0; i < GO_ST; i++) {
                mbar_wait(full + 8 * s2, ph2);
                const uint32_t st = s0 + s2 * GO_STAGE;
                const uint64_t dA = make_desc(st + w * 8192, 16, 1024), dB = make_desc(st + 16384, 8192, 1024);
                wgmma_fence();
                #pragma unroll
                for (int k = 0; k < 4; k++) wgmma_ss_n128<0, 1>(accL, desc_add(dA, k * 32), desc_add(dB, k * 2048), 1);
                if (i == 0) {
                    wgmma_commit();
                    wgmma_wait<1>();
                    const int sp = s == 0 ? GO_ST - 1 : s - 1;
                    if (wq < 2 && lane == 0) mbar_arrive_cta(empty + 8 * sp, wq);
                }
                if (++s2 == GO_ST) { s2 = 0; ph2 ^= 1; }
            }
            wgmma_commit();
            s2 = s;
            #pragma unroll
            for (int i = 0; i < GO_ST; i++) {
                const uint32_t st = s0 + s2 * GO_STAGE;
                const uint64_t dA = make_desc(st + w * 8192, 16, 1024), dB = make_desc(st + 16384, 8192, 1024);
                #pragma unroll
                for (int k = 0; k < 4; k++) wgmma_ss_n128<0, 1>(accH, desc_add(dA, k * 32), desc_add(dB, 16384 + k * 2048), 1);
                if (++s2 == GO_ST) s2 = 0;
            }
            wgmma_commit();
        }
        const int r = (lane & 7) + ((lane >> 3) & 1) * 8;
        auto epi = [&](const float (&a)[64], uint32_t stg, int col0) {
            const uint32_t rowa = stg + (wq * 16 + r) * 128;
            #pragma unroll
            for (int j = 0; j < 16; j += 2) {
                const int cg = j + (lane >> 4);
                stmatrix_x4(rowa + (cg >> 3) * 8192 + (((cg & 7) ^ (lane & 7)) << 4),
                    pack_bf16(a[4 * j], a[4 * j + 1]), pack_bf16(a[4 * j + 2], a[4 * j + 3]),
                    pack_bf16(a[4 * j + 4], a[4 * j + 5]), pack_bf16(a[4 * j + 6], a[4 * j + 7]));
            }
            bar_sync(3 + w, 128);
            if (wq == 0 && elect_one()) {
                fence_proxy_async();
                tma_red_add_2d(&mH, stg + (ks & 1) * 8192, col0 + (ks & 1) * 64, rowblk * 128 + w * 64);
                tma_red_add_2d(&mH, stg + ((ks & 1) ^ 1) * 8192, col0 + ((ks & 1) ^ 1) * 64, rowblk * 128 + w * 64);
                tma_commit();
            }
        };
        wgmma_wait<1>();
        fence_regs(accL);
        GTS();
        epi(accL, sStg + w * 16384, nh * 256);
        wgmma_wait<0>();
        fence_regs(accH);
        GTS();
        if (wq < 2 && lane == 0) {
            for (int i = 0; i < GO_ST; i++) mbar_arrive_cta(empty + 8 * i, wq);
        }
        bar_sync(1, 256);
        epi(accH, s0 + w * 16384, nh * 256 + 128);
        GTS();
        if (wq == 0 && elect_one()) { tma_wait<0>(); GTS(); TL_END(2); }
    }
}

constexpr int G1_SMEM = 65536 + 8 * 16384 + 16384 + 1024 + 64 + 512 + 64;

__global__ void __launch_bounds__(384, 1)
k_g1(const __grid_constant__ CUtensorMap mH, const __grid_constant__ CUtensorMap mW1, const __grid_constant__ CUtensorMap mT1,
     float2* __restrict__ stats, const float* __restrict__ cs1, float2* __restrict__ x1stat) {
    TL_START(3);
    GTS_DECL
    GTS();
    extern __shared__ uint8_t smem_raw[];
    const uint32_t sA = (smem_u32(smem_raw) + 1023) & ~1023u;
    const uint32_t sBm = sA + 65536, sStg = sBm + 8 * 16384, full = sStg + 16384, sStat = full + 64;
    const int warp = __shfl_sync(0xffffffffu, threadIdx.x >> 5, 0);
    const int lane = threadIdx.x & 31;
    const int rb = blockIdx.x >> 2, nq = blockIdx.x & 3;
    if (warp == 0 && elect_one()) {
        for (int i = 0; i < 8; i++) mbar_init(full + 8 * i, 1);
        fence_mbar_init();
        fence_proxy_async();
        for (int kb = 0; kb < 8; kb++) {
            mbar_expect_tx(full + 8 * kb, 16384 + 8192);
            tma_load_3d(sBm + kb * 16384, &mW1, full + 8 * kb, 0, kb * 64, nq * 2);
        }
        prefetch_tmap(&mH); prefetch_tmap(&mT1);
    }
    __syncthreads();
    pdl_launch();
    if (warp < 4) {
        if (warp == 0 && elect_one()) {
            pdl_wait();
            if (true) { TL_MARK(3); }
            for (int kb = 0; kb < 8; kb++) tma_load_2d(sA + kb * 8192, &mH, full + 8 * kb, kb * 64, rb * 64);
        }
    } else {
        const int w = (warp >> 2) - 1, wq = warp & 3;
        pdl_wait();
        float cs[16];
        #pragma unroll
        for (int j = 0; j < 8; j++) {
            const float2 t = __ldcg(reinterpret_cast<const float2*>(cs1 + nq * 128 + w * 64 + j * 8 + (lane & 3) * 2));
            cs[2 * j] = t.x; cs[2 * j + 1] = t.y;
        }
        const int srow = (warp - 4) * 8 + (lane >> 2);
        uint32_t soff[2];
        #pragma unroll
        for (int i = 0; i < 2; i++) soff[i] = sA + srow * 128 + ((((lane & 3) * 2 + i) ^ (srow & 7)) << 4);
        float sm0 = 0.f, sm1 = 0.f, sq0 = 0.f, sq1 = 0.f, shift = 0.f;
        float acc[32];
        const uint64_t dA = make_desc(sA, 16, 1024);
        #pragma unroll
        for (int kb = 0; kb < 8; kb++) {
            mbar_wait(full + 8 * kb, 0);
            if (kb == 0) { TL_FIRST(3); }
            if (kb == 0) GTS();
            wgmma_fence();
            const uint64_t dB = make_desc(sBm + kb * 16384 + w * 8192, 8192, 1024);
            #pragma unroll
            for (int k = 0; k < 4; k++) wgmma_ss_n64<0, 1>(acc, desc_add(dA, kb * 8192 + k * 32), desc_add(dB, k * 2048), (kb | k) != 0);
            wgmma_commit();
            const uint4 v0 = lds128(soff[0] + kb * 8192), v1 = lds128(soff[1] + kb * 8192);
            if (kb == 0) shift = __shfl_sync(0xffffffffu, __uint_as_float(v0.x << 16), lane & ~3);
            float f0[8], f1[8]; unpack8(v0, f0); unpack8(v1, f1);
            #pragma unroll
            for (int e = 0; e < 8; e++) {
                const float a = f0[e] - shift, b = f1[e] - shift;
                sm0 += a; sm1 += b; sq0 = fmaf(a, a, sq0); sq1 = fmaf(b, b, sq1);
            }
        }
        {
            float sm = sm0 + sm1, sq = sq0 + sq1;
            sm += __shfl_xor_sync(0xffffffffu, sm, 1); sq += __shfl_xor_sync(0xffffffffu, sq, 1);
            sm += __shfl_xor_sync(0xffffffffu, sm, 2); sq += __shfl_xor_sync(0xffffffffu, sq, 2);
            const float dm = sm * (1.f / DM);
            const float var = fmaxf(sq * (1.f / DM) - dm * dm, 0.f), mean = dm + shift;
            const float rstd = rsqrtf(var + LN_EPS);
            const float sc = 0.5f * rstd * rsqrtf(var * rstd * rstd + LN_EPS);
            if ((lane & 3) == 0) {
                asm volatile("st.shared.v2.f32 [%0], {%1, %2};" :: "r"(sStat + srow * 8), "f"(mean), "f"(sc) : "memory");
                if (nq == 0) { stats[rb * 64 + srow] = make_float2(mean, rstd); x1stat[rb * 64 + srow] = make_float2(0.f, 0.f); }
            }
        }
        bar_sync(1, 256);
        float mean0, sc0, mean1, sc1;
        asm volatile("ld.shared.v2.f32 {%0, %1}, [%2];" : "=f"(mean0), "=f"(sc0) : "r"(sStat + (wq * 16 + (lane >> 2)) * 8));
        asm volatile("ld.shared.v2.f32 {%0, %1}, [%2];" : "=f"(mean1), "=f"(sc1) : "r"(sStat + (wq * 16 + (lane >> 2) + 8) * 8));
        wgmma_wait<0>();
        fence_regs(acc);
        GTS();
        #pragma unroll
        for (int j = 0; j < 8; j++) {
            acc[4 * j]     = gelu_half(fmaf(-mean0, cs[2 * j],     acc[4 * j])     * sc0);
            acc[4 * j + 1] = gelu_half(fmaf(-mean0, cs[2 * j + 1], acc[4 * j + 1]) * sc0);
            acc[4 * j + 2] = gelu_half(fmaf(-mean1, cs[2 * j],     acc[4 * j + 2]) * sc1);
            acc[4 * j + 3] = gelu_half(fmaf(-mean1, cs[2 * j + 1], acc[4 * j + 3]) * sc1);
        }
        const int r = (lane & 7) + ((lane >> 3) & 1) * 8;
        const uint32_t rowa = sStg + w * 8192 + (wq * 16 + r) * 128;
        #pragma unroll
        for (int j = 0; j < 8; j += 2) {
            const int cg = j + (lane >> 4);
            stmatrix_x4(rowa + ((cg ^ (lane & 7)) << 4),
                pack_bf16(acc[4 * j], acc[4 * j + 1]), pack_bf16(acc[4 * j + 2], acc[4 * j + 3]),
                pack_bf16(acc[4 * j + 4], acc[4 * j + 5]), pack_bf16(acc[4 * j + 6], acc[4 * j + 7]));
        }
        bar_sync(3 + w, 128);
        if (wq == 0 && elect_one()) {
            fence_proxy_async();
            tma_store_2d(&mT1, sStg + w * 8192, nq * 128 + w * 64, rb * 64);
            tma_commit();
            GTS();
            tma_wait<0>();
            GTS();
            TL_END(3);
        }
    }
}

constexpr int GS_ST = 4;
constexpr int GS_STAGE = 32768 + 16384;
constexpr int GS_SMEM = GS_ST * GS_STAGE + 16384 + 1024 + 256;

template<int MODE>
__global__ void __cluster_dims__(2, 1, 1) __launch_bounds__(384, 1)
k_gs(const __grid_constant__ CUtensorMap mA, const __grid_constant__ CUtensorMap mW, const __grid_constant__ CUtensorMap mOut,
     const __grid_constant__ CUtensorMap mBase,
     const bf16* __restrict__ h, const float2* __restrict__ stats, const bf16* __restrict__ x1, float2* __restrict__ x1stat) {
    TL_START((MODE == 0 ? 4 : 6));
    GTS_DECL
    GTS();
    constexpr int NKB = MODE == 0 ? 4 : FF / 128;
    extern __shared__ uint8_t smem_raw[];
    const uint32_t s0 = (smem_u32(smem_raw) + 1023) & ~1023u;
    const uint32_t sStg = s0 + GS_ST * GS_STAGE, full = sStg + 16384, empty = full + 8 * GS_ST;
    const int warp = __shfl_sync(0xffffffffu, threadIdx.x >> 5, 0);
    const int lane = threadIdx.x & 31;
    const uint32_t rank = cluster_ctarank();
    const int rb = blockIdx.x >> 3, nt = blockIdx.x & 7;
    if (warp == 0 && elect_one()) {
        for (int i = 0; i < GS_ST; i++) { mbar_init(full + 8 * i, 1); mbar_init(empty + 8 * i, 4); }
        fence_mbar_init();
        fence_proxy_async();
        for (int kb = 0; kb < GS_ST; kb++) {
            mbar_expect_tx(full + 8 * kb, GS_STAGE);
            tma_load_2d(s0 + kb * GS_STAGE + 32768, &mW, full + 8 * kb, nt * 64, kb * 128);
        }
        prefetch_tmap(&mA); prefetch_tmap(&mOut);
    }
    __syncthreads();
    cluster_sync_relaxed();
    pdl_launch();
    if (warp < 4) {
        if (warp == 0 && elect_one()) {
            pdl_wait();
            if (true) { TL_MARK((MODE == 0 ? 4 : 6)); }
            int s = 0, ph = 1;
            for (int kb = 0; kb < NKB; kb++) {
                const uint32_t st = s0 + s * GS_STAGE;
                if (kb >= GS_ST) {
                    mbar_wait(empty + 8 * s, ph);
                    mbar_expect_tx(full + 8 * s, GS_STAGE);
                    tma_load_2d(st + 32768, &mW, full + 8 * s, nt * 64, kb * 128);
                }
                const int shift = MODE == 0 ? (kb == 0 ? -1 : (kb == 1 ? 1 : (kb == 2 ? -2 : 2))) : 0;
                tma_load_3d_mc(st + rank * 16384, &mA, full + 8 * s, 0, rb * 128 + rank * 64 + shift, kb * 2, (uint16_t)3);
                if (++s == GS_ST) { s = 0; ph ^= 1; }
            }
            if (NKB > GS_ST) for (int i = 0; i < GS_ST; i++) { mbar_wait(empty + 8 * s, ph); if (++s == GS_ST) { s = 0; ph ^= 1; } }
        }
    } else {
        const int w = (warp >> 2) - 1, wq = warp & 3;
        const int row0 = rb * 128 + w * 64 + wq * 16 + (lane >> 2), col0 = nt * 64 + (lane & 3) * 2;
        uint32_t ra[16], rb2[16];
        float2 st0, st1;
        float acc[32];
        int s = 0, ph = 0;
        auto kstep = [&](int kb) {
            mbar_wait(full + 8 * s, ph);
            if (kb == 0) { TL_FIRST((MODE == 0 ? 4 : 6)); }
            if (kb == 0) GTS();
            const uint32_t st = s0 + s * GS_STAGE;
            const uint64_t dA = make_desc(st + w * 16384, 16, 1024), dB = make_desc(st + 32768, 8192, 1024);
            wgmma_fence();
            #pragma unroll
            for (int k = 0; k < 8; k++)
                wgmma_ss_n64<0, 1>(acc, desc_add(dA, (k >> 2) * 8192 + (k & 3) * 32), desc_add(dB, k * 2048), (kb | k) != 0);
            wgmma_commit();
            if (NKB > GS_ST) {
                wgmma_wait<1>();
                if (kb > 0) { const int sp = s == 0 ? GS_ST - 1 : s - 1; if (wq < 2 && lane == 0) mbar_arrive_cta(empty + 8 * sp, wq); }
            }
            if (++s == GS_ST) { s = 0; ph ^= 1; }
        };
        #pragma unroll
        for (int kb = 0; kb < 4; kb++) {
            kstep(kb);
            #pragma unroll
            for (int j = 2 * kb; j < 2 * kb + 2; j++) {
                ra[2 * j] = __ldcg(reinterpret_cast<const uint32_t*>(h + (size_t)row0 * DM + col0 + j * 8));
                ra[2 * j + 1] = __ldcg(reinterpret_cast<const uint32_t*>(h + (size_t)(row0 + 8) * DM + col0 + j * 8));
                if (MODE == 1) {
                    rb2[2 * j] = __ldcg(reinterpret_cast<const uint32_t*>(x1 + (size_t)row0 * DM + col0 + j * 8));
                    rb2[2 * j + 1] = __ldcg(reinterpret_cast<const uint32_t*>(x1 + (size_t)(row0 + 8) * DM + col0 + j * 8));
                }
            }
            if (MODE == 0 && kb == 0) { st0 = __ldcg(stats + row0); st1 = __ldcg(stats + row0 + 8); }
        }
        for (int kb = 4; kb < NKB; kb++) kstep(kb);
        wgmma_wait<0>();
        fence_regs(acc);
        GTS();
        if (NKB > GS_ST) { const int sp = s == 0 ? GS_ST - 1 : s - 1; if (wq < 2 && lane == 0) mbar_arrive_cta(empty + 8 * sp, wq); }
        #pragma unroll
        for (int j = 0; j < 8; j++) {
            float r0 = bf_lo(ra[2 * j]), r1 = bf_hi(ra[2 * j]), r2 = bf_lo(ra[2 * j + 1]), r3 = bf_hi(ra[2 * j + 1]);
            if (MODE == 0) {
                r0 = (r0 - st0.x) * st0.y; r1 = (r1 - st0.x) * st0.y; r2 = (r2 - st1.x) * st1.y; r3 = (r3 - st1.x) * st1.y;
            } else {
                r0 += bf_lo(rb2[2 * j]); r1 += bf_hi(rb2[2 * j]); r2 += bf_lo(rb2[2 * j + 1]); r3 += bf_hi(rb2[2 * j + 1]);
            }
            acc[4 * j] += r0; acc[4 * j + 1] += r1; acc[4 * j + 2] += r2; acc[4 * j + 3] += r3;
        }
        const int r = (lane & 7) + ((lane >> 3) & 1) * 8;
        const uint32_t rowa = sStg + w * 8192 + (wq * 16 + r) * 128;
        #pragma unroll
        for (int j = 0; j < 8; j += 2) {
            const int cg = j + (lane >> 4);
            stmatrix_x4(rowa + ((cg ^ (lane & 7)) << 4),
                pack_bf16(acc[4 * j], acc[4 * j + 1]), pack_bf16(acc[4 * j + 2], acc[4 * j + 3]),
                pack_bf16(acc[4 * j + 4], acc[4 * j + 5]), pack_bf16(acc[4 * j + 6], acc[4 * j + 7]));
        }
        if (MODE == 0) {
            bar_sync(1, 256);
            const uint32_t rowb = s0 + w * 8192 + (wq * 16 + r) * 128;
            #pragma unroll
            for (int j = 0; j < 8; j += 2) {
                const int cg = j + (lane >> 4);
                stmatrix_x4(rowb + ((cg ^ (lane & 7)) << 4),
                    pack_bf16(acc[4 * j] + bf_lo(ra[2 * j]), acc[4 * j + 1] + bf_hi(ra[2 * j])),
                    pack_bf16(acc[4 * j + 2] + bf_lo(ra[2 * j + 1]), acc[4 * j + 3] + bf_hi(ra[2 * j + 1])),
                    pack_bf16(acc[4 * j + 4] + bf_lo(ra[2 * j + 2]), acc[4 * j + 5] + bf_hi(ra[2 * j + 2])),
                    pack_bf16(acc[4 * j + 6] + bf_lo(ra[2 * j + 3]), acc[4 * j + 7] + bf_hi(ra[2 * j + 3])));
            }
            float a0 = 0.f, q0 = 0.f, a1 = 0.f, q1 = 0.f;
            #pragma unroll
            for (int j = 0; j < 8; j++) {
                a0 += acc[4 * j] + acc[4 * j + 1]; q0 = fmaf(acc[4 * j], acc[4 * j], fmaf(acc[4 * j + 1], acc[4 * j + 1], q0));
                a1 += acc[4 * j + 2] + acc[4 * j + 3]; q1 = fmaf(acc[4 * j + 2], acc[4 * j + 2], fmaf(acc[4 * j + 3], acc[4 * j + 3], q1));
            }
            a0 = quad_sum(a0); q0 = quad_sum(q0); a1 = quad_sum(a1); q1 = quad_sum(q1);
            if ((lane & 3) == 0) {
                atomicAdd(&x1stat[row0].x, a0); atomicAdd(&x1stat[row0].y, q0);
                atomicAdd(&x1stat[row0 + 8].x, a1); atomicAdd(&x1stat[row0 + 8].y, q1);
            }
        }
        bar_sync(3 + w, 128);
        if (wq == 0 && elect_one()) {
            fence_proxy_async();
            tma_store_2d(&mOut, sStg + w * 8192, nt * 64, rb * 128 + w * 64);
            if (MODE == 0) tma_store_2d(&mBase, s0 + w * 8192, nt * 64, rb * 128 + w * 64);
            tma_commit();
            GTS();
            tma_wait<0>();
            GTS();
            TL_END((MODE == 0 ? 4 : 6));
        }
        if (MODE == 0) {
        }
    }
}

constexpr int ML_ST = 4;
constexpr int ML_SMEM = 131072 + ML_ST * 16384 + 32768 + 1024 + 128 + 896
;

__global__ void __cluster_dims__(2, 1, 1) __launch_bounds__(384, 1)
k_mlp(const __grid_constant__ CUtensorMap mX1, const __grid_constant__ CUtensorMap mW3, const __grid_constant__ CUtensorMap mW4,
      const __grid_constant__ CUtensorMap mOut, const float* __restrict__ cs3, const float2* __restrict__ x1stat) {
    TL_START(5);
    GTS_DECL
    GTS();
    extern __shared__ uint8_t smem_raw[];
    const uint32_t sA = (smem_u32(smem_raw) + 1023) & ~1023u;
    const uint32_t sBst = sA + 131072, sU = sBst + ML_ST * 16384, full = sU + 32768, empty = full + 8 * ML_ST, afull = empty + 8 * ML_ST, sCs = afull + 64;
    const int warp = __shfl_sync(0xffffffffu, threadIdx.x >> 5, 0);
    const int lane = threadIdx.x & 31;
    const uint32_t rank = cluster_ctarank();
    const int cl = blockIdx.x >> 1;
    const int rb = (cl >> 3) * 2 + rank, nt = cl & 7;
    const int ncol = nt * 224;
    if (warp == 0 && elect_one()) {
        for (int i = 0; i < ML_ST; i++) { mbar_init(full + 8 * i, 1); mbar_init(empty + 8 * i, 4); }
        for (int i = 0; i < 8; i++) mbar_init(afull + 8 * i, 1);
        fence_mbar_init();
        fence_proxy_async();
        prefetch_tmap(&mX1); prefetch_tmap(&mW3); prefetch_tmap(&mW4); prefetch_tmap(&mOut);
    }
    __syncthreads();
    cluster_sync_relaxed();
    pdl_launch();
    if (warp < 4) {
        reg_dealloc<40>();
        if (warp == 0 && elect_one()) {
            auto load_w = [&](int i, int s) {
                mbar_expect_tx(full + 8 * s, 16384);
                const uint32_t dst = sBst + s * 16384 + rank * 8192;
                if (i < 16) tma_load_2d_mc(dst, &mW3, full + 8 * s, ncol + (i >> 3) * 128 + rank * 64, (i & 7) * 64, (uint16_t)3);
                else        tma_load_2d_mc(dst, &mW4, full + 8 * s, ((i - 16) >> 2) * 128 + rank * 64, ncol + (i & 3) * 64, (uint16_t)3);
            };
            for (int i = 0; i < ML_ST; i++) load_w(i, i);
            pdl_wait();
            if (true) { TL_MARK(5); }
            for (int c = 0; c < 8; c++) {
                mbar_expect_tx(afull + 8 * c, 16384);
                tma_load_2d(sA + c * 16384, &mX1, afull + 8 * c, c * 64, rb * 128);
            }
            int s = 0, ph = 0;
            for (int i = ML_ST; i < 32; i++) {
                mbar_wait(empty + 8 * s, ph);
                load_w(i, s);
                if (++s == ML_ST) { s = 0; ph ^= 1; }
            }
            for (int i = 0; i < ML_ST; i++) { mbar_wait(empty + 8 * s, ph); if (++s == ML_ST) { s = 0; ph ^= 1; } }
        }
    } else {
        reg_alloc<232>();
        const int w = (warp >> 2) - 1, wq = warp & 3;
        float sc0, sc1, mean0, mean1;
        pdl_wait();
        {
            const int ct = threadIdx.x - 128;
            if (ct < 224) { const float v = __ldcg(cs3 + ncol + ct); asm volatile("st.shared.f32 [%0], %1;" :: "r"(sCs + 4 * ct), "f"(v) : "memory"); }
            const int row0 = rb * 128 + w * 64 + wq * 16 + (lane >> 2);
            const float2 s0 = __ldcg(x1stat + row0), s1 = __ldcg(x1stat + row0 + 8);
            mean0 = s0.x * (1.f / DM); mean1 = s1.x * (1.f / DM);
            sc0 = 0.5f * rsqrtf(fmaxf(s0.y * (1.f / DM) - mean0 * mean0, 0.f) + LN_EPS);
            sc1 = 0.5f * rsqrtf(fmaxf(s1.y * (1.f / DM) - mean1 * mean1, 0.f) + LN_EPS);
            bar_sync(1, 256);
        }
        int s = 0, ph = 0;
        const int r = (lane & 7) + ((lane >> 3) & 1) * 8;
        const uint32_t rowoff = w * 8192 + (wq * 16 + r) * 128;
        auto release = [&](int stage) { if (wq < 2 && lane == 0) mbar_arrive_cta(empty + 8 * stage, wq); };
        auto advance = [&]() { if (++s == ML_ST) { s = 0; ph ^= 1; } };
        {
            float acc0[64], acc1[48];
            const uint64_t dA = make_desc(sA + w * 8192, 16, 1024);
            const uint32_t csa = sCs + (lane & 3) * 8;
            auto ldcs = [&](int col) { float2 v; asm volatile("ld.shared.v2.f32 {%0, %1}, [%2];" : "=f"(v.x), "=f"(v.y) : "r"(csa + col * 4)); return v; };
            auto act = [&](const float* a, int col, uint32_t dst, int cg) {
                const float2 c0 = ldcs(col), c1 = ldcs(col + 8);
                stmatrix_x4(dst + rowoff + (((cg & 7) ^ (lane & 7)) << 4),
                    pack_bf16(gelu_half(fmaf(-mean0, c0.x, a[0]) * sc0), gelu_half(fmaf(-mean0, c0.y, a[1]) * sc0)),
                    pack_bf16(gelu_half(fmaf(-mean1, c0.x, a[2]) * sc1), gelu_half(fmaf(-mean1, c0.y, a[3]) * sc1)),
                    pack_bf16(gelu_half(fmaf(-mean0, c1.x, a[4]) * sc0), gelu_half(fmaf(-mean0, c1.y, a[5]) * sc0)),
                    pack_bf16(gelu_half(fmaf(-mean1, c1.x, a[6]) * sc1), gelu_half(fmaf(-mean1, c1.y, a[7]) * sc1)));
            };
            #pragma unroll
            for (int i = 0; i < 16; i++) {
                const int t = i >> 3, kb = i & 7;
                if (t == 0) mbar_wait(afull + 8 * kb, 0);
                mbar_wait(full + 8 * s, ph);
                if (i == 0) { TL_FIRST(5); GTS(); }
                const uint64_t dB = make_desc(sBst + s * 16384, 8192, 1024);
                wgmma_fence();
                #pragma unroll
                for (int k = 0; k < 4; k++) {
                    if (t == 0) wgmma_ss_n128<0, 1>(acc0, desc_add(dA, kb * 16384 + k * 32), desc_add(dB, k * 2048), (kb | k) != 0);
                    else        wgmma_ss_n96<0, 1>(acc1, desc_add(dA, kb * 16384 + k * 32), desc_add(dB, k * 2048), (kb | k) != 0);
                }
                wgmma_commit();
                wgmma_wait<1>();
                if (i > 0) release(s == 0 ? ML_ST - 1 : s - 1);
                advance();
                if (t == 1) {
                    if (kb == 0) fence_regs(acc0);
                    const int cg = 2 * kb + (lane >> 4);
                    act(&acc0[8 * kb], 16 * kb, sU + (kb >> 2) * 16384, cg);
                }
            }
            wgmma_wait<0>();
            fence_regs(acc1);
            release(s == 0 ? ML_ST - 1 : s - 1);
            GTS();
            #pragma unroll
            for (int j = 0; j < 6; j++) {
                const int cg = 2 * j + (lane >> 4);
                act(&acc1[8 * j], 128 + 16 * j, sA + (j >> 2) * 16384, cg);
            }
            fence_proxy_async();
            bar_sync(3 + w, 128);
            GTS();
        }
        {
            float accA[64], accB[64];
            const uint64_t dU01 = make_desc(sU + w * 8192, 16, 1024), dU23 = make_desc(sA + w * 8192, 16, 1024);
            auto epi_slices = [&](const float (&a)[64], int t, int j0, int j1) {
                const uint32_t stg = sA + 32768 + (t & 1) * 32768 + w * 16384 + (wq * 16 + r) * 128;
                #pragma unroll
                for (int j2 = j0; j2 < j1; j2++) {
                    const int j = 2 * j2, cg = j + (lane >> 4);
                    stmatrix_x4(stg + (cg >> 3) * 8192 + (((cg & 7) ^ (lane & 7)) << 4),
                        pack_bf16(a[4 * j], a[4 * j + 1]), pack_bf16(a[4 * j + 2], a[4 * j + 3]),
                        pack_bf16(a[4 * j + 4], a[4 * j + 5]), pack_bf16(a[4 * j + 6], a[4 * j + 7]));
                }
            };
            auto epi_issue = [&](int t) {
                bar_sync(3 + w, 128);
                if (wq == 0 && elect_one()) {
                    fence_proxy_async();
                    const uint32_t stg = sA + 32768 + (t & 1) * 32768 + w * 16384;
                    const int c = (nt & 1);
                    tma_red_add_2d(&mOut, stg + c * 8192, t * 128 + c * 64, rb * 128 + w * 64);
                    tma_red_add_2d(&mOut, stg + (c ^ 1) * 8192, t * 128 + (c ^ 1) * 64, rb * 128 + w * 64);
                    tma_commit();
                }
            };
            auto tile = [&](float (&cur)[64], float (&prev)[64], int t) {
                #pragma unroll
                for (int kb = 0; kb < 4; kb++) {
                    mbar_wait(full + 8 * s, ph);
                    const uint64_t dB = make_desc(sBst + s * 16384, 8192, 1024);
                    const uint64_t dU = desc_add(kb < 2 ? dU01 : dU23, (kb & 1) * 16384);
                    wgmma_fence();
                    #pragma unroll
                    for (int k = 0; k < (kb == 3 ? 2 : 4); k++)
                        wgmma_ss_n128<0, 1>(cur, desc_add(dU, k * 32), desc_add(dB, k * 2048), (kb | k) != 0);
                    wgmma_commit();
                    const int scur = s, sprev = s == 0 ? ML_ST - 1 : s - 1;
                    advance();
                    if (kb > 0) { wgmma_wait<1>(); release(sprev); }
                    if (t > 0) {
                        if (kb == 0 && t > 2) { if (wq == 0 && elect_one()) tma_wait_read<1>(); bar_sync(3 + w, 128); }
                        epi_slices(prev, t - 1, 2 * kb, 2 * kb + 2);
                        if (kb == 3) epi_issue(t - 1);
                    }
                    if (kb == 3) { wgmma_wait<0>(); fence_regs(cur); release(scur); }
                }
            };
            tile(accA, accB, 0);
            tile(accB, accA, 1);
            tile(accA, accB, 2);
            tile(accB, accA, 3);
            GTS();
            if (wq == 0 && elect_one()) tma_wait_read<1>();
            bar_sync(3 + w, 128);
            epi_slices(accB, 3, 0, 8);
            epi_issue(3);
            GTS();
            if (wq == 0 && elect_one()) { tma_wait<0>(); GTS(); TL_END(5); }
        }
    }
}
__device__ __align__(1024) bf16  g_qkv[3 * NH * S_LEN * HD];
__device__ __align__(1024) bf16  g_ctx[S_LEN * NH * HD];
__device__ __align__(1024) bf16  g_h[S_LEN * DM];
__device__ __align__(1024) float2 g_stats[S_LEN];
__device__ __align__(1024) float g_colsum[DM + FF];
__device__ __align__(1024) float2 g_x1stat[S_LEN];
__device__ __align__(1024) bf16  g_t1[S_LEN * DM];
__device__ __align__(1024) bf16  g_x1[S_LEN * DM];

typedef CUresult (*EncodeTiledFn)(CUtensorMap*, CUtensorMapDataType, cuuint32_t, void*, const cuuint64_t*, const cuuint64_t*,
                                  const cuuint32_t*, const cuuint32_t*, CUtensorMapInterleave, CUtensorMapSwizzle,
                                  CUtensorMapL2promotion, CUtensorMapFloatOOBfill);
static EncodeTiledFn g_encode = nullptr;

static CUtensorMap make_map(const void* ptr, int rank, const uint64_t* dims, const uint64_t* strides, const uint32_t* box,
                            CUtensorMapSwizzle sw = CU_TENSOR_MAP_SWIZZLE_128B) {
    const CUtensorMapDataType dt = CU_TENSOR_MAP_DATA_TYPE_BFLOAT16;
    CUtensorMap m;
    cuuint64_t d[3], st[2]; cuuint32_t b[3], es[3] = {1, 1, 1};
    for (int i = 0; i < rank; i++) { d[i] = dims[i]; b[i] = box[i]; }
    for (int i = 0; i < rank - 1; i++) st[i] = strides[i];
    g_encode(&m, dt, rank, (void*)ptr, d, st, b, es, CU_TENSOR_MAP_INTERLEAVE_NONE, sw,
             CU_TENSOR_MAP_L2_PROMOTION_L2_256B, CU_TENSOR_MAP_FLOAT_OOB_FILL_NONE);
    return m;
}
static CUtensorMap map2d(const void* p, uint64_t cols, uint64_t rows, uint32_t box_cols, uint32_t box_rows) {
    uint64_t d[2] = {cols, rows}, s[1] = {cols * 2}; uint32_t b[2] = {box_cols, box_rows};
    return make_map(p, 2, d, s, b);
}
static CUtensorMap map3d(const void* p, uint64_t cols, uint64_t rows, uint32_t box_rows, uint32_t nchunks) {
    uint64_t d[3] = {64, rows, cols / 64}, s[2] = {cols * 2, 128}; uint32_t b[3] = {64, box_rows, nchunks};
    return make_map(p, 3, d, s, b);
}

template<typename... KArgs, typename... Args>
static void launch(void (*kern)(KArgs...), int grid, int smem, cudaStream_t st, bool pdl, Args... args) {
    cudaLaunchConfig_t cfg = {};
    cfg.gridDim = dim3(grid); cfg.blockDim = dim3(384); cfg.dynamicSmemBytes = smem; cfg.stream = st;
    cudaLaunchAttribute at[1];
    at[0].id = cudaLaunchAttributeProgrammaticStreamSerialization;
    at[0].val.programmaticStreamSerializationAllowed = 1;
    cfg.attrs = at; cfg.numAttrs = pdl ? 1 : 0;
    cudaLaunchKernelEx(&cfg, kern, KArgs(args)...);
}

#define USE_PDL 1

struct Plan {
    CUtensorMap mX, mC, mWq, mWk, mWv, mQkvOut, mQkvIn, mCtxOut, mCtxIn, mWo, mH, mW1, mT1out, mT1in, mW2, mX1out, mX1in, mW3, mW4, mOut;
    bf16 *qkv, *ctx, *t1, *x1, *h; float2 *stats, *x1stat; float* colsum;
    AttnSched sched; int attn_grid;
};

static void build_sched(Plan& p, int sms) {
    AttnSched& sc = p.sched;
    for (int i = 0; i < 160; i++) { sc.e[i].x = 0; sc.e[i].y = 0; }
    auto add = [&](int b, int h, int q) {
        const int n = (int)(sc.e[b].y >> 48);
        const unsigned long long v = (unsigned long long)(h * 16 + q);
        if (n < 4) sc.e[b].x |= v << (16 * n); else sc.e[b].y |= v << (16 * (n - 4));
        sc.e[b].y += 1ull << 48;
    };
#define SCHED_MODE 1
    if (sms == 132 && SCHED_MODE == 1) {
        p.attn_grid = 132;
        int b = 0;
        for (int h = 0; h < 8; h++) for (int i = 0; i < 8; i++) { add(b, h, 15 - i); add(b, h, i); b++; }
        for (int h = 8; h < 16; h++) { add(b++, h, 15); for (int i = 0; i < 7; i++) { add(b, h, 14 - i); add(b, h, i); b++; } }
        for (int h = 8; h < 16; h += 2) { add(b, h, 7); add(b, h + 1, 7); b++; }
        b = 64; int r = 0;
        for (int h = 16; h < 25; h++) for (int i = 0; i < 8; i++) {
            if (i == 0 && h < 20) { add(r++, h, 15); continue; }
            add(b, h, 15 - i); add(b, h, i); b++;
        }
        for (int h = 25; h < 32; h++) { add(r++, h, 15); for (int i = 0; i < 7; i++) { add(r, h, 14 - i); add(r, h, i); r++; } }
        for (int h = 25; h < 31; h += 2) { add(r, h, 7); add(r, h + 1, 7); r++; }
        add(r, 31, 7); for (int h = 16; h < 20; h++) add(r, h, 0);
    } else {
        p.attn_grid = sms < 86 ? 86 : (sms > 160 ? 160 : sms);
        for (int q = 0; q < NH * 8; q++) { const int b = q % p.attn_grid; add(b, q >> 3, 15 - (q & 7)); add(b, q >> 3, q & 7); }
    }
}

static void build_plan(Plan& p, void* const* d_in, void* d_out) {
    if (!g_encode) {
        void* fn = nullptr; cudaDriverEntryPointQueryResult qr;
        cudaGetDriverEntryPoint("cuTensorMapEncodeTiled", &fn, cudaEnableDefault, &qr);
        g_encode = (EncodeTiledFn)fn;
        cudaFuncSetAttribute(k_qkv, cudaFuncAttributeMaxDynamicSharedMemorySize, QK_SMEM);
        cudaFuncSetAttribute(k_attn, cudaFuncAttributeMaxDynamicSharedMemorySize, AT_SMEM);
        cudaFuncSetAttribute(k_oproj, cudaFuncAttributeMaxDynamicSharedMemorySize, GO_SMEM);
        cudaFuncSetAttribute(k_g1, cudaFuncAttributeMaxDynamicSharedMemorySize, G1_SMEM);
        cudaFuncSetAttribute(k_gs<0>, cudaFuncAttributeMaxDynamicSharedMemorySize, GS_SMEM);
        cudaFuncSetAttribute(k_mlp, cudaFuncAttributeMaxDynamicSharedMemorySize, ML_SMEM);
    }
    { int dev = 0, sms = 132; cudaGetDevice(&dev); cudaDeviceGetAttribute(&sms, cudaDevAttrMultiProcessorCount, dev); build_sched(p, sms); }
    cudaGetSymbolAddress((void**)&p.qkv, g_qkv); cudaGetSymbolAddress((void**)&p.ctx, g_ctx);
    cudaGetSymbolAddress((void**)&p.h, g_h); cudaGetSymbolAddress((void**)&p.stats, g_stats); cudaGetSymbolAddress((void**)&p.colsum, g_colsum); cudaGetSymbolAddress((void**)&p.x1stat, g_x1stat);
    cudaGetSymbolAddress((void**)&p.t1, g_t1); cudaGetSymbolAddress((void**)&p.x1, g_x1);
    p.mX = map2d(d_in[0], DM, S_LEN, 64, 128);
    p.mC = map2d(d_in[1], DM, S_LEN, 64, 128);
    p.mWq = map2d(d_in[2], NH * HD, DM, 64, 64);
    p.mWk = map2d(d_in[3], NH * HD, DM, 64, 64);
    p.mWv = map2d(d_in[4], NH * HD, DM, 64, 64);
    p.mQkvOut = map2d(p.qkv, HD, 3 * NH * S_LEN, 64, 64);
    p.mQkvIn = map3d(p.qkv, HD, 3 * NH * S_LEN, 128, 2);
    p.mCtxOut = map2d(p.ctx, NH * HD, S_LEN, 64, 64);
    p.mCtxIn = map2d(p.ctx, NH * HD, S_LEN, 64, 128);
    p.mWo = map3d(d_in[5], DM, NH * HD, 64, 2);
    p.mH = map2d(p.h, DM, S_LEN, 64, 64);
    p.mW1 = map3d(d_in[7], DM, DM, 64, 2);
    p.mT1out = map2d(p.t1, DM, S_LEN, 64, 64);
    p.mT1in = map3d(p.t1, DM, S_LEN, 64, 2);
    p.mW2 = map2d(d_in[8], DM, DM, 64, 128);
    p.mX1out = map2d(p.x1, DM, S_LEN, 64, 64);
    p.mX1in = map2d(p.x1, DM, S_LEN, 64, 128);
    p.mW3 = map2d(d_in[9], FF, DM, 64, 64);
    p.mW4 = map2d(d_in[10], DM, FF, 64, 64);
    p.mOut = map2d(d_out, DM, S_LEN, 64, 64);
}

static void run_stage(const Plan& p, int stage, void* const* d_in, cudaStream_t st, bool pdl) {
    switch (stage) {
    case 0: launch(k_qkv, 128, QK_SMEM, st, false, p.mX, p.mC, p.mWq, p.mWk, p.mWv, p.mQkvOut, (const bf16*)d_in[0], p.h, (const bf16*)d_in[2], (const bf16*)d_in[3], (const bf16*)d_in[4]); break;
    case 1: {
        PrefetchList pf;
        pf.ptr[0] = d_in[5]; pf.bytes[0] = NH * HD * DM * 2;
        pf.ptr[1] = d_in[7]; pf.bytes[1] = DM * DM * 2;
        pf.ptr[2] = d_in[8]; pf.bytes[2] = DM * DM * 2;
        pf.ptr[3] = d_in[9]; pf.bytes[3] = DM * FF * 2;
        pf.ptr[4] = d_in[10]; pf.bytes[4] = DM * FF * 2;
        pf.colsum = p.colsum; pf.qkv = p.qkv;
        launch(k_attn, p.attn_grid, AT_SMEM, st, pdl, p.mQkvIn, p.mCtxOut, pf, p.sched); break; }
    case 2: launch(k_oproj, 128, GO_SMEM, st, pdl, p.mCtxIn, p.mWo, p.mH); break;
    case 3: launch(k_g1, 128, G1_SMEM, st, pdl, p.mH, p.mW1, p.mT1out, p.stats, (const float*)p.colsum, p.x1stat); break;
    case 4: launch(k_gs<0>, 128, GS_SMEM, st, pdl, p.mT1in, p.mW2, p.mX1out, p.mOut, (const bf16*)p.h, (const float2*)p.stats, (const bf16*)nullptr, p.x1stat); break;
    case 5: launch(k_mlp, 128, ML_SMEM, st, pdl, p.mX1in, p.mW3, p.mW4, p.mOut, (const float*)(p.colsum + DM), (const float2*)p.x1stat); break;
    }
}

constexpr int NUM_STAGES = 6;
extern "C" void kernel_launch(void* const* d_in, const int* in_sizes, int n_in, void* d_out, int out_size) {
    Plan p;
    build_plan(p, d_in, d_out);
    cudaStream_t st = cudaStreamPerThread;
    for (int s = 0; s < NUM_STAGES; s++) run_stage(p, s, d_in, st, USE_PDL);
}
```

```cpp
#include <cuda_runtime.h>
#include <cuda_bf16.h>
#include <cuda.h>
#include <stdint.h>

typedef __nv_bfloat16 bf16;

constexpr int S_LEN = 2048;
constexpr int DM    = 512;
constexpr int NH    = 32;
constexpr int HD    = 128;
constexpr int FF    = 1792;
constexpr float LN_EPS = 1e-5f;
constexpr float AT_SCALE = 0.08838834764831845f * 1.4426950408889634f;

#define GTS_DECL
#define GTS()
#define PROF_DECL
#define PROF_TS(slot)
#define TL_START(k)
#define TL_MARK(k)
#define TL_END(k)
#define TL_FIRST(k)
#define SPIN_LIMIT (1u << 20)

__device__ __forceinline__ uint32_t smem_u32(const void* p) { return (uint32_t)__cvta_generic_to_shared(p); }
__device__ __forceinline__ uint32_t elect_one() {
    uint32_t pred;
    asm volatile("{\n.reg .pred px;\nelect.sync _|px, 0xFFFFFFFF;\nselp.u32 %0, 1, 0, px;\n}\n" : "=r"(pred));
    return pred;
}
__device__ __forceinline__ void mbar_init(uint32_t bar, uint32_t count) {
    asm volatile("mbarrier.init.shared::cta.b64 [%0], %1;" :: "r"(bar), "r"(count) : "memory");
}
__device__ __forceinline__ void mbar_expect_tx(uint32_t bar, uint32_t bytes) {
    asm volatile("mbarrier.arrive.expect_tx.shared::cta.b64 _, [%0], %1;" :: "r"(bar), "r"(bytes) : "memory");
}
__device__ __forceinline__ void mbar_arrive(uint32_t bar) {
    asm volatile("mbarrier.arrive.shared::cta.b64 _, [%0];" :: "r"(bar) : "memory");
}
__device__ __forceinline__ void mbar_arrive_if(uint32_t bar, uint32_t flag) {
    asm volatile("{\n.reg .pred p;\nsetp.ne.b32 p, %1, 0;\n@p mbarrier.arrive.shared::cta.b64 _, [%0];\n}" :: "r"(bar), "r"(flag) : "memory");
}
__device__ __forceinline__ void mbar_arrive_cta(uint32_t bar, uint32_t cta) {
    asm volatile("{\n.reg .b32 ra;\nmapa.shared::cluster.u32 ra, %0, %1;\n"
                 "mbarrier.arrive.shared::cluster.b64 _, [ra];\n}" :: "r"(bar), "r"(cta) : "memory");
}
__device__ __forceinline__ bool mbar_try_wait(uint32_t bar, uint32_t parity) {
    uint32_t ok;
    asm volatile("{\n.reg .pred p;\nmbarrier.try_wait.parity.shared::cta.b64 p, [%1], %2;\nselp.u32 %0, 1, 0, p;\n}"
                 : "=r"(ok) : "r"(bar), "r"(parity) : "memory");
    return ok;
}
__device__ __forceinline__ bool mbar_test(uint32_t bar, uint32_t parity) {
    uint32_t ok;
    asm volatile("{\n.reg .pred p;\nmbarrier.test_wait.parity.shared::cta.b64 p, [%1], %2;\nselp.u32 %0, 1, 0, p;\n}"
                 : "=r"(ok) : "r"(bar), "r"(parity) : "memory");
    return ok;
}
__device__ __forceinline__ void mbar_wait(uint32_t bar, uint32_t parity) {
    uint32_t n = 0;
    while (!mbar_try_wait(bar, parity) && ++n < SPIN_LIMIT) { }
}
__device__ __forceinline__ bool mbar_try_wait_cl(uint32_t bar, uint32_t parity) {
    uint32_t ok;
    asm volatile("{\n.reg .pred p;\nmbarrier.try_wait.parity.shared::cta.b64 p, [%1], %2;\nselp.u32 %0, 1, 0, p;\n}"
                 : "=r"(ok) : "r"(bar), "r"(parity) : "memory");
    return ok;
}
__device__ __forceinline__ void mbar_wait_cl(uint32_t bar, uint32_t parity) {
    uint32_t n = 0;
    while (!mbar_try_wait_cl(bar, parity) && ++n < SPIN_LIMIT) { }
}
__device__ __forceinline__ void fence_mbar_init() { asm volatile("fence.mbarrier_init.release.cluster;" ::: "memory"); }
__device__ __forceinline__ void fence_proxy_async() { asm volatile("fence.proxy.async.shared::cta;" ::: "memory"); }
__device__ __forceinline__ void fence_proxy_async_all() { asm volatile("fence.proxy.async;" ::: "memory"); }

__device__ __forceinline__ void tma_load_2d(uint32_t dst, const CUtensorMap* map, uint32_t bar, int c0, int c1) {
    asm volatile("cp.async.bulk.tensor.2d.shared::cluster.global.mbarrier::complete_tx::bytes [%0], [%1, {%3, %4}], [%2];"
        :: "r"(dst), "l"(map), "r"(bar), "r"(c0), "r"(c1) : "memory");
}
__device__ __forceinline__ void tma_load_3d(uint32_t dst, const CUtensorMap* map, uint32_t bar, int c0, int c1, int c2) {
    asm volatile("cp.async.bulk.tensor.3d.shared::cluster.global.mbarrier::complete_tx::bytes [%0], [%1, {%3, %4, %5}], [%2];"
        :: "r"(dst), "l"(map), "r"(bar), "r"(c0), "r"(c1), "r"(c2) : "memory");
}
__device__ __forceinline__ void tma_load_2d_mc(uint32_t dst, const CUtensorMap* map, uint32_t bar, int c0, int c1, uint16_t mask) {
    asm volatile("cp.async.bulk.tensor.2d.shared::cluster.global.mbarrier::complete_tx::bytes.multicast::cluster [%0], [%1, {%3, %4}], [%2], %5;"
        :: "r"(dst), "l"(map), "r"(bar), "r"(c0), "r"(c1), "h"(mask) : "memory");
}
__device__ __forceinline__ void tma_load_3d_mc(uint32_t dst, const CUtensorMap* map, uint32_t bar, int c0, int c1, int c2, uint16_t mask) {
    asm volatile("cp.async.bulk.tensor.3d.shared::cluster.global.mbarrier::complete_tx::bytes.multicast::cluster [%0], [%1, {%3, %4, %5}], [%2], %6;"
        :: "r"(dst), "l"(map), "r"(bar), "r"(c0), "r"(c1), "r"(c2), "h"(mask) : "memory");
}
__device__ __forceinline__ void tma_store_2d(const CUtensorMap* map, uint32_t src, int c0, int c1) {
    asm volatile("cp.async.bulk.tensor.2d.global.shared::cta.bulk_group [%0, {%2, %3}], [%1];"
        :: "l"(map), "r"(src), "r"(c0), "r"(c1) : "memory");
}
__device__ __forceinline__ void tma_store_2d_hint(const CUtensorMap* map, uint32_t src, int c0, int c1, uint64_t pol) {
    asm volatile("cp.async.bulk.tensor.2d.global.shared::cta.bulk_group.L2::cache_hint [%0, {%2, %3}], [%1], %4;"
        :: "l"(map), "r"(src), "r"(c0), "r"(c1), "l"(pol) : "memory");
}
__device__ __forceinline__ uint64_t policy_evict_first() {
    uint64_t p; asm volatile("createpolicy.fractional.L2::evict_first.b64 %0, 1.0;" : "=l"(p)); return p;
}
__device__ __forceinline__ void tma_store_3d(const CUtensorMap* map, uint32_t src, int c0, int c1, int c2) {
    asm volatile("cp.async.bulk.tensor.3d.global.shared::cta.bulk_group [%0, {%2, %3, %4}], [%1];"
        :: "l"(map), "r"(src), "r"(c0), "r"(c1), "r"(c2) : "memory");
}
__device__ __forceinline__ void tma_red_add_2d(const CUtensorMap* map, uint32_t src, int c0, int c1) {
    asm volatile("cp.reduce.async.bulk.tensor.2d.global.shared::cta.add.bulk_group [%0, {%2, %3}], [%1];"
        :: "l"(map), "r"(src), "r"(c0), "r"(c1) : "memory");
}
__device__ __forceinline__ void tma_prefetch_2d(const CUtensorMap* map, int c0, int c1) {
    asm volatile("cp.async.bulk.prefetch.tensor.2d.L2.global [%0, {%1, %2}];" :: "l"(map), "r"(c0), "r"(c1) : "memory");
}
__device__ __forceinline__ void l2_prefetch(const void* p, uint32_t bytes) {
    asm volatile("cp.async.bulk.prefetch.L2.global [%0], %1;" :: "l"(p), "r"(bytes) : "memory");
}
__device__ __forceinline__ void prefetch_l2(const void* p) { asm volatile("prefetch.global.L2 [%0];" :: "l"(p)); }
__device__ __forceinline__ void tma_commit() { asm volatile("cp.async.bulk.commit_group;" ::: "memory"); }
template<int N> __device__ __forceinline__ void tma_wait_read() { asm volatile("cp.async.bulk.wait_group.read %0;" :: "n"(N) : "memory"); }
template<int N> __device__ __forceinline__ void tma_wait() { asm volatile("cp.async.bulk.wait_group %0;" :: "n"(N) : "memory"); }
__device__ __forceinline__ void prefetch_tmap(const CUtensorMap* map) {
    asm volatile("prefetch.tensormap [%0];" :: "l"(map) : "memory");
}

__device__ __forceinline__ void wgmma_fence() { asm volatile("wgmma.fence.sync.aligned;" ::: "memory"); }
__device__ __forceinline__ void wgmma_commit() { asm volatile("wgmma.commit_group.sync.aligned;" ::: "memory"); }
template<int N> __device__ __forceinline__ void wgmma_wait() { asm volatile("wgmma.wait_group.sync.aligned %0;" :: "n"(N) : "memory"); }

template<int N> __device__ __forceinline__ void fence_regs(float (&d)[N]) {
    #pragma unroll
    for (int i = 0; i < N; i++) asm volatile("" : "+f"(d[i]) :: "memory");
}
template<int N> __device__ __forceinline__ void fence_regs(uint32_t (&d)[N]) {
    #pragma unroll
    for (int i = 0; i < N; i++) asm volatile("" : "+r"(d[i]) :: "memory");
}

__device__ __forceinline__ uint64_t make_desc(uint32_t addr, uint32_t lbo_bytes, uint32_t sbo_bytes) {
    uint64_t d = 0;
    d |= (uint64_t)((addr & 0x3FFFF) >> 4);
    d |= (uint64_t)((lbo_bytes & 0x3FFFF) >> 4) << 16;
    d |= (uint64_t)((sbo_bytes & 0x3FFFF) >> 4) << 32;
    d |= (uint64_t)1 << 62;
    return d;
}
__device__ __forceinline__ uint64_t desc_add(uint64_t d, uint32_t bytes) {
    return d + (uint64_t)(bytes >> 4);
}

__device__ __forceinline__ void bar_sync(int id, int n) { asm volatile("bar.sync %0, %1;" :: "r"(id), "r"(n) : "memory"); }
__device__ __forceinline__ void bar_arrive(int id, int n) { asm volatile("bar.arrive %0, %1;" :: "r"(id), "r"(n) : "memory"); }
__device__ __forceinline__ bool bar_red_or(int id, int n, bool v) {
    uint32_t r;
    asm volatile("{\n.reg .pred p, q;\nsetp.ne.u32 q, %3, 0;\nbar.red.or.pred p, %1, %2, q;\nselp.u32 %0, 1, 0, p;\n}"
                 : "=r"(r) : "r"(id), "r"(n), "r"((uint32_t)v) : "memory");
    return r;
}
template<int R> __device__ __forceinline__ void reg_alloc() { asm volatile("setmaxnreg.inc.sync.aligned.u32 %0;" :: "n"(R)); }
template<int R> __device__ __forceinline__ void reg_dealloc() { asm volatile("setmaxnreg.dec.sync.aligned.u32 %0;" :: "n"(R)); }
__device__ __forceinline__ uint32_t cluster_ctarank() { uint32_t r; asm volatile("mov.u32 %0, %%cluster_ctarank;" : "=r"(r)); return r; }
__device__ __forceinline__ void cluster_arrive() { asm volatile("barrier.cluster.arrive.release.aligned;" ::: "memory"); }
__device__ __forceinline__ void cluster_wait() { asm volatile("barrier.cluster.wait.acquire.aligned;" ::: "memory"); }
__device__ __forceinline__ void pdl_wait() { asm volatile("griddepcontrol.wait;" ::: "memory"); }
__device__ __forceinline__ void pdl_launch() { asm volatile("griddepcontrol.launch_dependents;" ::: "memory"); }

__device__ __forceinline__ uint32_t pack_bf16(float lo, float hi) {
    uint32_t r;
    asm("cvt.rn.bf16x2.f32 %0, %1, %2;" : "=r"(r) : "f"(hi), "f"(lo));
    return r;
}
__device__ __forceinline__ float ex2(float x) {
    float y;
    asm("ex2.approx.ftz.f32 %0, %1;" : "=f"(y) : "f"(x));
    return y;
}
__device__ __forceinline__ void stmatrix_x4(uint32_t addr, uint32_t r0, uint32_t r1, uint32_t r2, uint32_t r3) {
    asm volatile("stmatrix.sync.aligned.m8n8.x4.shared.b16 [%0], {%1, %2, %3, %4};"
        :: "r"(addr), "r"(r0), "r"(r1), "r"(r2), "r"(r3) : "memory");
}
template<int TA, int TB> __device__ __forceinline__ void wgmma_ss_n128(float (&d)[64], uint64_t descA, uint64_t descB, int scaleD) {
    asm volatile("{\n.reg .pred p;\n"
        "setp.ne.b32 p, %66, 0;\n"
        "wgmma.mma_async.sync.aligned.m64n128k16.f32.bf16.bf16 "
        "{%0,%1,%2,%3,%4,%5,%6,%7,%8,%9,%10,%11,%12,%13,%14,%15,%16,%17,%18,%19,%20,%21,%22,%23,%24,%25,%26,%27,%28,%29,%30,%31,%32,%33,%34,%35,%36,%37,%38,%39,%40,%41,%42,%43,%44,%45,%46,%47,%48,%49,%50,%51,%52,%53,%54,%55,%56,%57,%58,%59,%60,%61,%62,%63}, "
        "%64, %65, p, 1, 1, %67, %68;\n}\n"
        : "+f"(d[0]),"+f"(d[1]),"+f"(d[2]),"+f"(d[3]),"+f"(d[4]),"+f"(d[5]),"+f"(d[6]),"+f"(d[7]),"+f"(d[8]),"+f"(d[9]),"+f"(d[10]),"+f"(d[11]),"+f"(d[12]),"+f"(d[13]),"+f"(d[14]),"+f"(d[15]),"+f"(d[16]),"+f"(d[17]),"+f"(d[18]),"+f"(d[19]),"+f"(d[20]),"+f"(d[21]),"+f"(d[22]),"+f"(d[23]),"+f"(d[24]),"+f"(d[25]),"+f"(d[26]),"+f"(d[27]),"+f"(d[28]),"+f"(d[29]),"+f"(d[30]),"+f"(d[31]),"+f"(d[32]),"+f"(d[33]),"+f"(d[34]),"+f"(d[35]),"+f"(d[36]),"+f"(d[37]),"+f"(d[38]),"+f"(d[39]),"+f"(d[40]),"+f"(d[41]),"+f"(d[42]),"+f"(d[43]),"+f"(d[44]),"+f"(d[45]),"+f"(d[46]),"+f"(d[47]),"+f"(d[48]),"+f"(d[49]),"+f"(d[50]),"+f"(d[51]),"+f"(d[52]),"+f"(d[53]),"+f"(d[54]),"+f"(d[55]),"+f"(d[56]),"+f"(d[57]),"+f"(d[58]),"+f"(d[59]),"+f"(d[60]),"+f"(d[61]),"+f"(d[62]),"+f"(d[63])
        : "l"(descA), "l"(descB), "r"(scaleD), "n"(TA), "n"(TB));
}
template<int TB> __device__ __forceinline__ void wgmma_rs_n128(float (&d)[64], uint32_t a0, uint32_t a1, uint32_t a2, uint32_t a3, uint64_t descB, int scaleD) {
    asm volatile("{\n.reg .pred p;\n"
        "setp.ne.b32 p, %69, 0;\n"
        "wgmma.mma_async.sync.aligned.m64n128k16.f32.bf16.bf16 "
        "{%0,%1,%2,%3,%4,%5,%6,%7,%8,%9,%10,%11,%12,%13,%14,%15,%16,%17,%18,%19,%20,%21,%22,%23,%24,%25,%26,%27,%28,%29,%30,%31,%32,%33,%34,%35,%36,%37,%38,%39,%40,%41,%42,%43,%44,%45,%46,%47,%48,%49,%50,%51,%52,%53,%54,%55,%56,%57,%58,%59,%60,%61,%62,%63}, "
        "{%64,%65,%66,%67}, %68, p, 1, 1, %70;\n}\n"
        : "+f"(d[0]),"+f"(d[1]),"+f"(d[2]),"+f"(d[3]),"+f"(d[4]),"+f"(d[5]),"+f"(d[6]),"+f"(d[7]),"+f"(d[8]),"+f"(d[9]),"+f"(d[10]),"+f"(d[11]),"+f"(d[12]),"+f"(d[13]),"+f"(d[14]),"+f"(d[15]),"+f"(d[16]),"+f"(d[17]),"+f"(d[18]),"+f"(d[19]),"+f"(d[20]),"+f"(d[21]),"+f"(d[22]),"+f"(d[23]),"+f"(d[24]),"+f"(d[25]),"+f"(d[26]),"+f"(d[27]),"+f"(d[28]),"+f"(d[29]),"+f"(d[30]),"+f"(d[31]),"+f"(d[32]),"+f"(d[33]),"+f"(d[34]),"+f"(d[35]),"+f"(d[36]),"+f"(d[37]),"+f"(d[38]),"+f"(d[39]),"+f"(d[40]),"+f"(d[41]),"+f"(d[42]),"+f"(d[43]),"+f"(d[44]),"+f"(d[45]),"+f"(d[46]),"+f"(d[47]),"+f"(d[48]),"+f"(d[49]),"+f"(d[50]),"+f"(d[51]),"+f"(d[52]),"+f"(d[53]),"+f"(d[54]),"+f"(d[55]),"+f"(d[56]),"+f"(d[57]),"+f"(d[58]),"+f"(d[59]),"+f"(d[60]),"+f"(d[61]),"+f"(d[62]),"+f"(d[63])
        : "r"(a0), "r"(a1), "r"(a2), "r"(a3), "l"(descB), "r"(scaleD), "n"(TB));
}
template<int TA, int TB> __device__ __forceinline__ void wgmma_ss_n256(float (&d)[128], uint64_t descA, uint64_t descB, int scaleD) {
    asm volatile("{\n.reg .pred p;\n"
        "setp.ne.b32 p, %130, 0;\n"
        "wgmma.mma_async.sync.aligned.m64n256k16.f32.bf16.bf16 "
        "{%0,%1,%2,%3,%4,%5,%6,%7,%8,%9,%10,%11,%12,%13,%14,%15,%16,%17,%18,%19,%20,%21,%22,%23,%24,%25,%26,%27,%28,%29,%30,%31,%32,%33,%34,%35,%36,%37,%38,%39,%40,%41,%42,%43,%44,%45,%46,%47,%48,%49,%50,%51,%52,%53,%54,%55,%56,%57,%58,%59,%60,%61,%62,%63,%64,%65,%66,%67,%68,%69,%70,%71,%72,%73,%74,%75,%76,%77,%78,%79,%80,%81,%82,%83,%84,%85,%86,%87,%88,%89,%90,%91,%92,%93,%94,%95,%96,%97,%98,%99,%100,%101,%102,%103,%104,%105,%106,%107,%108,%109,%110,%111,%112,%113,%114,%115,%116,%117,%118,%119,%120,%121,%122,%123,%124,%125,%126,%127}, "
        "%128, %129, p, 1, 1, %131, %132;\n}\n"
        : "+f"(d[0]),"+f"(d[1]),"+f"(d[2]),"+f"(d[3]),"+f"(d[4]),"+f"(d[5]),"+f"(d[6]),"+f"(d[7]),"+f"(d[8]),"+f"(d[9]),"+f"(d[10]),"+f"(d[11]),"+f"(d[12]),"+f"(d[13]),"+f"(d[14]),"+f"(d[15]),"+f"(d[16]),"+f"(d[17]),"+f"(d[18]),"+f"(d[19]),"+f"(d[20]),"+f"(d[21]),"+f"(d[22]),"+f"(d[23]),"+f"(d[24]),"+f"(d[25]),"+f"(d[26]),"+f"(d[27]),"+f"(d[28]),"+f"(d[29]),"+f"(d[30]),"+f"(d[31]),"+f"(d[32]),"+f"(d[33]),"+f"(d[34]),"+f"(d[35]),"+f"(d[36]),"+f"(d[37]),"+f"(d[38]),"+f"(d[39]),"+f"(d[40]),"+f"(d[41]),"+f"(d[42]),"+f"(d[43]),"+f"(d[44]),"+f"(d[45]),"+f"(d[46]),"+f"(d[47]),"+f"(d[48]),"+f"(d[49]),"+f"(d[50]),"+f"(d[51]),"+f"(d[52]),"+f"(d[53]),"+f"(d[54]),"+f"(d[55]),"+f"(d[56]),"+f"(d[57]),"+f"(d[58]),"+f"(d[59]),"+f"(d[60]),"+f"(d[61]),"+f"(d[62]),"+f"(d[63]),"+f"(d[64]),"+f"(d[65]),"+f"(d[66]),"+f"(d[67]),"+f"(d[68]),"+f"(d[69]),"+f"(d[70]),"+f"(d[71]),"+f"(d[72]),"+f"(d[73]),"+f"(d[74]),"+f"(d[75]),"+f"(d[76]),"+f"(d[77]),"+f"(d[78]),"+f"(d[79]),"+f"(d[80]),"+f"(d[81]),"+f"(d[82]),"+f"(d[83]),"+f"(d[84]),"+f"(d[85]),"+f"(d[86]),"+f"(d[87]),"+f"(d[88]),"+f"(d[89]),"+f"(d[90]),"+f"(d[91]),"+f"(d[92]),"+f"(d[93]),"+f"(d[94]),"+f"(d[95]),"+f"(d[96]),"+f"(d[97]),"+f"(d[98]),"+f"(d[99]),"+f"(d[100]),"+f"(d[101]),"+f"(d[102]),"+f"(d[103]),"+f"(d[104]),"+f"(d[105]),"+f"(d[106]),"+f"(d[107]),"+f"(d[108]),"+f"(d[109]),"+f"(d[110]),"+f"(d[111]),"+f"(d[112]),"+f"(d[113]),"+f"(d[114]),"+f"(d[115]),"+f"(d[116]),"+f"(d[117]),"+f"(d[118]),"+f"(d[119]),"+f"(d[120]),"+f"(d[121]),"+f"(d[122]),"+f"(d[123]),"+f"(d[124]),"+f"(d[125]),"+f"(d[126]),"+f"(d[127])
        : "l"(descA), "l"(descB), "r"(scaleD), "n"(TA), "n"(TB));
}
template<int TA, int TB> __device__ __forceinline__ void wgmma_ss_n64(float (&d)[32], uint64_t descA, uint64_t descB, int scaleD) {
    asm volatile("{\n.reg .pred p;\n"
        "setp.ne.b32 p, %34, 0;\n"
        "wgmma.mma_async.sync.aligned.m64n64k16.f32.bf16.bf16 "
        "{%0,%1,%2,%3,%4,%5,%6,%7,%8,%9,%10,%11,%12,%13,%14,%15,%16,%17,%18,%19,%20,%21,%22,%23,%24,%25,%26,%27,%28,%29,%30,%31}, "
        "%32, %33, p, 1, 1, %35, %36;\n}\n"
        : "+f"(d[0]),"+f"(d[1]),"+f"(d[2]),"+f"(d[3]),"+f"(d[4]),"+f"(d[5]),"+f"(d[6]),"+f"(d[7]),"+f"(d[8]),"+f"(d[9]),"+f"(d[10]),"+f"(d[11]),"+f"(d[12]),"+f"(d[13]),"+f"(d[14]),"+f"(d[15]),"+f"(d[16]),"+f"(d[17]),"+f"(d[18]),"+f"(d[19]),"+f"(d[20]),"+f"(d[21]),"+f"(d[22]),"+f"(d[23]),"+f"(d[24]),"+f"(d[25]),"+f"(d[26]),"+f"(d[27]),"+f"(d[28]),"+f"(d[29]),"+f"(d[30]),"+f"(d[31])
        : "l"(descA), "l"(descB), "r"(scaleD), "n"(TA), "n"(TB));
}
template<int TA, int TB> __device__ __forceinline__ void wgmma_ss_n96(float (&d)[48], uint64_t descA, uint64_t descB, int scaleD) {
    asm volatile("{\n.reg .pred p;\n"
        "setp.ne.b32 p, %50, 0;\n"
        "wgmma.mma_async.sync.aligned.m64n96k16.f32.bf16.bf16 "
        "{%0,%1,%2,%3,%4,%5,%6,%7,%8,%9,%10,%11,%12,%13,%14,%15,%16,%17,%18,%19,%20,%21,%22,%23,%24,%25,%26,%27,%28,%29,%30,%31,%32,%33,%34,%35,%36,%37,%38,%39,%40,%41,%42,%43,%44,%45,%46,%47}, "
        "%48, %49, p, 1, 1, %51, %52;\n}\n"
        : "+f"(d[0]),"+f"(d[1]),"+f"(d[2]),"+f"(d[3]),"+f"(d[4]),"+f"(d[5]),"+f"(d[6]),"+f"(d[7]),"+f"(d[8]),"+f"(d[9]),"+f"(d[10]),"+f"(d[11]),"+f"(d[12]),"+f"(d[13]),"+f"(d[14]),"+f"(d[15]),"+f"(d[16]),"+f"(d[17]),"+f"(d[18]),"+f"(d[19]),"+f"(d[20]),"+f"(d[21]),"+f"(d[22]),"+f"(d[23]),"+f"(d[24]),"+f"(d[25]),"+f"(d[26]),"+f"(d[27]),"+f"(d[28]),"+f"(d[29]),"+f"(d[30]),"+f"(d[31]),"+f"(d[32]),"+f"(d[33]),"+f"(d[34]),"+f"(d[35]),"+f"(d[36]),"+f"(d[37]),"+f"(d[38]),"+f"(d[39]),"+f"(d[40]),"+f"(d[41]),"+f"(d[42]),"+f"(d[43]),"+f"(d[44]),"+f"(d[45]),"+f"(d[46]),"+f"(d[47])
        : "l"(descA), "l"(descB), "r"(scaleD), "n"(TA), "n"(TB));
}
constexpr int QK_PF = 2;
constexpr int QK_ST = 5;
constexpr int QK_A_BYTES = 128 * 512 * 2;
constexpr int QK_B_BYTES = 64 * 128 * 2;
constexpr int QK_STG = 2 * 64 * 64 * 2;
constexpr int QK_SMEM = QK_A_BYTES + QK_ST * QK_B_BYTES + QK_STG + 1024 + 256
;

__device__ __forceinline__ void unpack8(const uint4& v, float (&f)[8]) {
    const uint32_t u[4] = {v.x, v.y, v.z, v.w};
    #pragma unroll
    for (int i = 0; i < 4; i++) { f[2 * i] = __uint_as_float(u[i] << 16); f[2 * i + 1] = __uint_as_float(u[i] & 0xffff0000u); }
}
__device__ __forceinline__ float warp_sum(float v) {
    #pragma unroll
    for (int o = 16; o > 0; o >>= 1) v += __shfl_xor_sync(0xffffffffu, v, o);
    return v;
}
__device__ __forceinline__ uint4 lds128(uint32_t a) {
    uint4 v; asm volatile("ld.shared.v4.u32 {%0,%1,%2,%3}, [%4];" : "=r"(v.x), "=r"(v.y), "=r"(v.z), "=r"(v.w) : "r"(a)); return v;
}
__device__ __forceinline__ void sts128(uint32_t a, const uint4& v) {
    asm volatile("st.shared.v4.u32 [%0], {%1,%2,%3,%4};" :: "r"(a), "r"(v.x), "r"(v.y), "r"(v.z), "r"(v.w) : "memory");
}
__device__ __forceinline__ uint4 pack8(const float (&f)[8], float sc) {
    uint4 o;
    o.x = pack_bf16(f[0] * sc, f[1] * sc); o.y = pack_bf16(f[2] * sc, f[3] * sc);
    o.z = pack_bf16(f[4] * sc, f[5] * sc); o.w = pack_bf16(f[6] * sc, f[7] * sc);
    return o;
}

__device__ __forceinline__ void ln_rows_inplace(uint32_t sA, int row_base, int lane, uint32_t afull, int nbar, int aph) {
    const int row = row_base + (lane >> 1);
    const uint32_t rowa = sA + row * 128;
    uint32_t off[4];
    #pragma unroll
    for (int i = 0; i < 4; i++) off[i] = rowa + ((((lane & 1) * 4 + i) ^ (row & 7)) << 4);
    float sm0 = 0.f, sm1 = 0.f, sq0 = 0.f, sq1 = 0.f, shift = 0.f;
    #pragma unroll 1
    for (int c = 0; c < 8; c++) {
        if (c < nbar) mbar_wait(afull + 8 * c, aph);
        uint4 v[4];
        #pragma unroll
        for (int i = 0; i < 4; i++) v[i] = lds128(off[i] + c * 16384);
        if (c == 0) shift = __shfl_sync(0xffffffffu, __uint_as_float(v[0].x << 16), lane & ~1);
        #pragma unroll
        for (int i = 0; i < 4; i++) {
            float f[8]; unpack8(v[i], f);
            #pragma unroll
            for (int e = 0; e < 8; e += 2) {
                const float a = f[e] - shift, b = f[e + 1] - shift;
                sm0 += a; sm1 += b; sq0 = fmaf(a, a, sq0); sq1 = fmaf(b, b, sq1);
            }
        }
    }
    float sm = sm0 + sm1, sq = sq0 + sq1;
    sm += __shfl_xor_sync(0xffffffffu, sm, 1); sq += __shfl_xor_sync(0xffffffffu, sq, 1);
    const float dm = sm * (1.f / DM);
    const float var = fmaxf(sq * (1.f / DM) - dm * dm, 0.f);
    const float rs = rsqrtf(var + LN_EPS), nb = -(dm + shift) * rs;
    #pragma unroll 2
    for (int c = 0; c < 8; c++) {
        uint4 v[4];
        #pragma unroll
        for (int i = 0; i < 4; i++) v[i] = lds128(off[i] + c * 16384);
        #pragma unroll
        for (int i = 0; i < 4; i++) {
            float f[8]; unpack8(v[i], f);
            uint4 o;
            o.x = pack_bf16(fmaf(f[0], rs, nb), fmaf(f[1], rs, nb)); o.y = pack_bf16(fmaf(f[2], rs, nb), fmaf(f[3], rs, nb));
            o.z = pack_bf16(fmaf(f[4], rs, nb), fmaf(f[5], rs, nb)); o.w = pack_bf16(fmaf(f[6], rs, nb), fmaf(f[7], rs, nb));
            sts128(off[i] + c * 16384, o);
        }
    }
}

__device__ __forceinline__ int qkv_tile_count(int g) { return g < 2 ? 11 : (g == 2 ? 10 : (g < 7 ? 13 : 12)); }
__device__ __forceinline__ int qkv_tile_id(int g, int i) {
    if (g < 3) return 31 - (3 * i + g);
    const int idx = 5 * i + (g - 3);
    return 32 * (1 + (idx & 1)) + 31 - (idx >> 1);
}
struct QkvCtx {
    uint32_t sA, sBst, sStg, full, empty, sfull, sempty;
    int s, ph;
    int sph;
    int w, wq, lane;
    float osc;
};

__device__ __forceinline__ void qkv_epi_slice(const float (&acc)[64], int j2, uint32_t stg_row, int lane, float sc) {
    const int j = 2 * j2;
    const int cg = (j & 7) + (lane >> 4);
    stmatrix_x4(stg_row + ((cg ^ (lane & 7)) << 4),
                pack_bf16(acc[4 * j] * sc, acc[4 * j + 1] * sc), pack_bf16(acc[4 * j + 2] * sc, acc[4 * j + 3] * sc),
                pack_bf16(acc[4 * j + 4] * sc, acc[4 * j + 5] * sc), pack_bf16(acc[4 * j + 6] * sc, acc[4 * j + 7] * sc));
}
__device__ __forceinline__ void qkv_stg_acquire(QkvCtx& c) { mbar_wait(c.sempty + 8 * c.w, c.sph ^ 1); }
__device__ __forceinline__ void qkv_stg_publish(QkvCtx& c) {
    __syncwarp();
    if (c.lane == 0) mbar_arrive(c.sfull + 8 * c.w);
    c.sph ^= 1;
}
__device__ __forceinline__ void qkv_release(const QkvCtx& c, int stage) {
    if (c.wq < 2 && c.lane == 0) mbar_arrive_cta(c.empty + 8 * stage, c.wq);
}

#define PROF_SKIP 0
#define QTS()
template<bool WAIT_A, bool HAS_PREV, int W>
__device__ __forceinline__ void qkv_tile(QkvCtx& c, float (&cur)[64], float (&prev)[64], uint32_t afull, int aph) {
    const uint64_t dA = make_desc(c.sA + c.w * 8192, 16, 1024);
    const int r = (c.lane & 7) + ((c.lane >> 3) & 1) * 8;
    const uint32_t stg_row = c.sStg + c.w * 8192 + (c.wq * 16 + r) * 128;
    #pragma unroll
    for (int kb = 0; kb < 8; kb++) {
        QTS();
        if (WAIT_A) mbar_wait(afull + 8 * kb, aph);
        mbar_wait(c.full + 8 * c.s, c.ph);
        if (WAIT_A && kb == 0) { TL_FIRST(0); }
        QTS();
        const uint64_t dB = make_desc(c.sBst + c.s * QK_B_BYTES, 8192, 1024);
        wgmma_fence();
        #pragma unroll
        for (int k = 0; k < 4; k++)
            wgmma_ss_n128<0, 1>(cur, desc_add(dA, kb * 16384 + k * 32), desc_add(dB, k * 2048), (kb | k) != 0);
        wgmma_commit();
        const int scur = c.s;
        const int sprev = c.s == 0 ? QK_ST - 1 : c.s - 1;
        if (++c.s == QK_ST) { c.s = 0; c.ph ^= 1; }
        QTS();
        if (kb > 0) { wgmma_wait<1>(); qkv_release(c, sprev); }
        QTS();
        if (HAS_PREV) {
            const int e = kb - 2 * W;
            if (e == 0 || e == 4) qkv_stg_acquire(c);
            if (e == 0 || e == 1 || e == 4 || e == 5) {
                const int j2 = (e >> 2) * 4 + (e & 1) * 2;
                qkv_epi_slice(prev, j2, stg_row, c.lane, c.osc); qkv_epi_slice(prev, j2 + 1, stg_row, c.lane, c.osc);
            }
            if (e == 1 || e == 5) qkv_stg_publish(c);
        }
        if (kb == 7) {
            wgmma_wait<0>();
            fence_regs(cur);
            qkv_release(c, scur);
        }
    }
}
__device__ __forceinline__ void qkv_drain(QkvCtx& c, float (&acc)[64]) {
    const int r = (c.lane & 7) + ((c.lane >> 3) & 1) * 8;
    const uint32_t stg_row = c.sStg + c.w * 8192 + (c.wq * 16 + r) * 128;
    #pragma unroll
    for (int h = 0; h < 2; h++) {
        qkv_stg_acquire(c);
        #pragma unroll
        for (int j = 0; j < 4; j++) qkv_epi_slice(acc, 4 * h + j, stg_row, c.lane, c.osc);
        qkv_stg_publish(c);
    }
}

__global__ void __cluster_dims__(2, 1, 1) __launch_bounds__(384, 1)
k_qkv(const __grid_constant__ CUtensorMap mX, const __grid_constant__ CUtensorMap mC,
      const __grid_constant__ CUtensorMap mWq, const __grid_constant__ CUtensorMap mWk,
      const __grid_constant__ CUtensorMap mWv, const __grid_constant__ CUtensorMap mOut,
      const bf16* __restrict__ x, bf16* __restrict__ hacc,
      const bf16* __restrict__ wq, const bf16* __restrict__ wk, const bf16* __restrict__ wv) {
    TL_START(0);
#define TS2()
    TS2();
    extern __shared__ uint8_t smem_raw[];
    const uint32_t sA = (smem_u32(smem_raw) + 1023) & ~1023u;
    const uint32_t sBst = sA + QK_A_BYTES, sStg = sBst + QK_ST * QK_B_BYTES, sB = sStg + QK_STG;
    const uint32_t full = sB, empty = full + 8 * QK_ST, afull = empty + 8 * QK_ST,
                   sfull = afull + 64, sempty = sfull + 16;
    const int warp = __shfl_sync(0xffffffffu, threadIdx.x >> 5, 0);
    const int lane = threadIdx.x & 31;
    const uint32_t rank = cluster_ctarank();
    const int cl = blockIdx.x >> 1;
    const int rowblk = (cl >> 3) * 2 + rank;
    const int g = cl & 7;
    const int ntile = qkv_tile_count(g);
    if (warp == 0 && elect_one()) {
        for (int i = 0; i < QK_ST; i++) { mbar_init(full + 8 * i, 1); mbar_init(empty + 8 * i, 4); }
        for (int i = 0; i < 8; i++) mbar_init(afull + 8 * i, 1);
        for (int i = 0; i < 2; i++) { mbar_init(sfull + 8 * i, 4); mbar_init(sempty + 8 * i, 1); }
        fence_mbar_init();
        fence_proxy_async();
        const CUtensorMap* mA = (g < 3) ? &mX : &mC;
        const int n_early = (g < 3) ? 8 : 2;
        for (int kb = 0; kb < n_early; kb++) {
            mbar_expect_tx(afull + 8 * kb, 16384);
            tma_load_2d(sA + kb * 16384, mA, afull + 8 * kb, kb * 64, rowblk * 128);
        }
    }
    __syncthreads();
    TS2();
    asm volatile("barrier.cluster.arrive.relaxed.aligned;" ::: "memory");
    cluster_wait();
    pdl_launch();
    TS2();

    if (warp < 4) {
        reg_dealloc<40>();
        if (warp == 0) {
            if (elect_one()) {
                int s = 0, ph = 1;
                for (int i = 0; i < ntile; i++) {
                    const int n = qkv_tile_id(g, i);
                    const CUtensorMap* mW = n < 32 ? &mWq : (n < 64 ? &mWk : &mWv);
                    const int col = (n & 31) * 128 + rank * 64;
                    for (int kb = 0; kb < 8; kb++) {
                        mbar_wait(empty + 8 * s, ph);
                        mbar_expect_tx(full + 8 * s, QK_B_BYTES);
                        tma_load_2d_mc(sBst + s * QK_B_BYTES + rank * 8192, mW, full + 8 * s, col, kb * 64, (uint16_t)3);
                        if (++s == QK_ST) { s = 0; ph ^= 1; }
                        if (i == 0 && g >= 3 && kb < 6) {
                            mbar_expect_tx(afull + 8 * (kb + 2), 16384);
                            tma_load_2d(sA + (kb + 2) * 16384, &mC, afull + 8 * (kb + 2), (kb + 2) * 64, rowblk * 128);
                        }
                    }
                }
                for (int i = 0; i < QK_ST; i++) { mbar_wait(empty + 8 * s, ph); if (++s == QK_ST) { s = 0; ph ^= 1; } }
            }
        } else if (warp < 3) {
            const int w = warp - 1;
            const bool leader = elect_one();
            for (int i = 0; i < 2 * ntile; i++) {
                if (leader) {
                    mbar_wait(sfull + 8 * w, i & 1);
                    fence_proxy_async();
                    tma_store_2d(&mOut, sStg + w * 8192, (i & 1) * 64, qkv_tile_id(g, i >> 1) * S_LEN + rowblk * 128 + w * 64);
                    tma_commit();
                }
                __syncwarp();
                const int ip = (i >> 1) + QK_PF + 1;
                if ((i & 1) == 0 && ip < ntile) {
                    const int np = qkv_tile_id(g, ip);
                    prefetch_l2((np < 32 ? wq : (np < 64 ? wk : wv)) + (size_t)((cl >> 3) * 64 + w * 32 + lane) * (NH * HD) + (np & 31) * 128 + rank * 64);
                }
                if (leader) {
                    tma_wait_read<0>();
                    mbar_arrive(sempty + 8 * w);
                }
            }
            if (leader) { tma_wait<0>(); TL_END(0); }
        } else {
            mbar_wait(afull + 8 * 7, 0);
            for (int i = 1; i < QK_PF + 1; i++) {
                const int np = qkv_tile_id(g, i);
                const bf16* wp = (np < 32 ? wq : (np < 64 ? wk : wv)) + (size_t)((cl >> 3) * 64 + lane) * (NH * HD) + (np & 31) * 128 + rank * 64;
                prefetch_l2(wp); prefetch_l2(wp + 32 * (NH * HD));
            }
            const uint4* xs = reinterpret_cast<const uint4*>(x + (size_t)blockIdx.x * 16 * DM);
            uint4* hd = reinterpret_cast<uint4*>(hacc + (size_t)blockIdx.x * 16 * DM);
            #pragma unroll 4
            for (int i = lane; i < 16 * DM / 8; i += 32) hd[i] = __ldg(xs + i);
        }
    } else {
        reg_alloc<232>();
        QkvCtx c;
        c.sA = sA; c.sBst = sBst; c.sStg = sStg; c.full = full; c.empty = empty; c.sfull = sfull; c.sempty = sempty;
        c.s = 0; c.ph = 0; c.sph = 0; c.w = (warp >> 2) - 1; c.wq = warp & 3; c.lane = lane;
        c.osc = g < 3 ? AT_SCALE : 1.f;
        float acc0[64], acc1[64];
        if (g < 3) {
            TS2();
            ln_rows_inplace(sA, c.w * 64 + c.wq * 16, lane, afull, 8, 0);
            TS2();
            fence_proxy_async();
            bar_sync(3 + c.w, 128);
            TS2();
        }
        if (c.w == 0) {
            qkv_tile<true, false, 0>(c, acc0, acc1, afull, 0);
            int i = 1;
            for (; i + 1 < ntile; i += 2) {
                qkv_tile<false, true, 0>(c, acc1, acc0, afull, 0);
                qkv_tile<false, true, 0>(c, acc0, acc1, afull, 0);
            }
            if (i < ntile) { qkv_tile<false, true, 0>(c, acc1, acc0, afull, 0); qkv_drain(c, acc1); }
            else qkv_drain(c, acc0);
        } else {
            qkv_tile<true, false, 1>(c, acc0, acc1, afull, 0);
            int i = 1;
            for (; i + 1 < ntile; i += 2) {
                qkv_tile<false, true, 1>(c, acc1, acc0, afull, 0);
                qkv_tile<false, true, 1>(c, acc0, acc1, afull, 0);
            }
            if (i < ntile) { qkv_tile<false, true, 1>(c, acc1, acc0, afull, 0); qkv_drain(c, acc1); }
            else qkv_drain(c, acc0);
        }
        TS2();
    }
}
constexpr int AT_KST = 2, AT_VST = 2;
constexpr int AT_TILE = 128 * 128 * 2;
constexpr int AT_SMEM = (3 + AT_KST + AT_VST) * AT_TILE + 1024 + 256
;
constexpr float AT_BIG = 1073741824.f;
#define AT_PINGPONG 1

struct PrefetchList { const void* ptr[5]; uint32_t bytes[5]; float* colsum; const bf16* qkv; };
#define AT_PFD 2
#define AT_WPF 10

struct AttnSched { ulonglong2 e[160]; };
#define attn_get_tile(t, head, qt) attn_get_tile_(my_list, (t), (head), (qt))
__device__ __forceinline__ bool attn_get_tile_(const ulonglong2& list, int t, int& head, int& qt) {
    if (t >= (int)(list.y >> 48)) return false;
    const int e = (int)((t < 4 ? list.x >> (16 * t) : list.y >> (16 * (t - 4))) & 0xffff);
    head = e >> 4; qt = e & 15;
    return true;
}

__device__ __forceinline__ void attn_qk(float (&S)[64], uint64_t dq, uint64_t dk) {
    #pragma unroll
    for (int k = 0; k < 8; k++) {
        const uint32_t off = (k >> 2) * 16384 + (k & 3) * 32;
        wgmma_ss_n128<0, 0>(S, desc_add(dq, off), desc_add(dk, off), k > 0);
    }
}
__device__ __forceinline__ void attn_pv(float (&O)[64], uint32_t (&P)[32], uint64_t dv, int acc) {
    #pragma unroll
    for (int k = 0; k < 8; k++)
        wgmma_rs_n128<1>(O, P[4 * k], P[4 * k + 1], P[4 * k + 2], P[4 * k + 3], desc_add(dv, k * 2048), k > 0 ? 1 : acc);
}
__device__ __forceinline__ float quad_max(float v) {
    v = fmaxf(v, __shfl_xor_sync(0xffffffffu, v, 1));
    return fmaxf(v, __shfl_xor_sync(0xffffffffu, v, 2));
}
__device__ __forceinline__ float quad_sum(float v) {
    v += __shfl_xor_sync(0xffffffffu, v, 1);
    return v + __shfl_xor_sync(0xffffffffu, v, 2);
}
__device__ __forceinline__ void attn_rowmax(const float (&S)[64], float& mx0, float& mx1) {
    float a0 = fmaxf(S[0], S[1]), a1 = fmaxf(S[2], S[3]), b0 = fmaxf(S[4], S[5]), b1 = fmaxf(S[6], S[7]);
    #pragma unroll
    for (int j = 2; j < 16; j += 2) {
        a0 = fmaxf(a0, fmaxf(S[4 * j], S[4 * j + 1]));
        a1 = fmaxf(a1, fmaxf(S[4 * j + 2], S[4 * j + 3]));
        b0 = fmaxf(b0, fmaxf(S[4 * j + 4], S[4 * j + 5]));
        b1 = fmaxf(b1, fmaxf(S[4 * j + 6], S[4 * j + 7]));
    }
    mx0 = quad_max(fmaxf(a0, b0));
    mx1 = quad_max(fmaxf(a1, b1));
}
__device__ __forceinline__ bool attn_first_max(const float (&S)[64], float& m0, float& m1) {
    attn_rowmax(S, m0, m1);
    const bool zero = __all_sync(0xffffffffu, fabsf(m0) <= 16.f && fabsf(m1) <= 16.f);
    if (zero) { m0 = 0.f; m1 = 0.f; }
    return zero;
}
template<bool ZERO>
__device__ __forceinline__ void attn_exp_pack_(float (&S)[64], float m0, float m1, uint32_t (&P)[32], float& s0, float& s1) {
    float a0 = 0.f, a1 = 0.f, b0 = 0.f, b1 = 0.f;
    #pragma unroll
    for (int j = 0; j < 16; j++) {
        if (!ZERO) { S[4 * j] -= m0; S[4 * j + 1] -= m0; S[4 * j + 2] -= m1; S[4 * j + 3] -= m1; }
        const float e0 = ex2(S[4 * j]), e1 = ex2(S[4 * j + 1]), e2 = ex2(S[4 * j + 2]), e3 = ex2(S[4 * j + 3]);
        a0 += e0; b0 += e1; a1 += e2; b1 += e3;
        P[2 * j] = pack_bf16(e0, e1); P[2 * j + 1] = pack_bf16(e2, e3);
    }
    s0 = a0 + b0; s1 = a1 + b1;
}
__device__ __forceinline__ void attn_exp_pack(float (&S)[64], float m0, float m1, bool zero, uint32_t (&P)[32], float& s0, float& s1) {
    if (zero) attn_exp_pack_<true>(S, m0, m1, P, s0, s1); else attn_exp_pack_<false>(S, m0, m1, P, s0, s1);
}
__device__ __forceinline__ void attn_exp_pack_shift(const float (&S)[64], float d0, float d1, uint32_t (&P)[32], float& s0, float& s1) {
    float a0 = 0.f, a1 = 0.f, b0 = 0.f, b1 = 0.f;
    #pragma unroll
    for (int j = 0; j < 16; j++) {
        const float e0 = ex2(S[4 * j] - d0), e1 = ex2(S[4 * j + 1] - d0), e2 = ex2(S[4 * j + 2] - d1), e3 = ex2(S[4 * j + 3] - d1);
        a0 += e0; b0 += e1; a1 += e2; b1 += e3;
        P[2 * j] = pack_bf16(e0, e1); P[2 * j + 1] = pack_bf16(e2, e3);
    }
    s0 = a0 + b0; s1 = a1 + b1;
}
__global__ void __launch_bounds__(384, 1)
k_attn(const __grid_constant__ CUtensorMap mQKV, const __grid_constant__ CUtensorMap mCtx, const PrefetchList pf,
       const __grid_constant__ AttnSched sched) {
    TL_START(1);
#define TS6()
    TS6();
    ulonglong2 my_list = sched.e[blockIdx.x];
    asm volatile("" : "+l"(my_list.x), "+l"(my_list.y));
    extern __shared__ uint8_t smem_raw[];
    const uint32_t sQ = (smem_u32(smem_raw) + 1023) & ~1023u;
    const uint32_t sK = sQ + 2 * AT_TILE, sV = sK + AT_KST * AT_TILE, sO = sV + AT_VST * AT_TILE, sB = sO + AT_TILE;
    const uint32_t qfull = sB, qempty = sB + 16, kfull = sB + 32, kempty = kfull + 8 * AT_KST,
                   vfull = kempty + 8 * AT_KST, vempty = vfull + 8 * AT_VST, ofull = vempty + 8 * AT_VST, oempty = ofull + 16, stepctr = oempty + 16;
    const int warp = __shfl_sync(0xffffffffu, threadIdx.x >> 5, 0);
    const int lane = threadIdx.x & 31;
    if (threadIdx.x == 0) {
        for (int i = 0; i < 2; i++) { mbar_init(qfull + 8 * i, 1); mbar_init(qempty + 8 * i, 2); mbar_init(ofull + 8 * i, 4); mbar_init(oempty + 8 * i, 1); }
        for (int i = 0; i < AT_KST; i++) { mbar_init(kfull + 8 * i, 1); mbar_init(kempty + 8 * i, 2); }
        for (int i = 0; i < AT_VST; i++) { mbar_init(vfull + 8 * i, 1); mbar_init(vempty + 8 * i, 2); }
        asm volatile("st.shared.u32 [%0], %1;" :: "r"(stepctr), "r"(0) : "memory");
        fence_mbar_init();
        prefetch_tmap(&mQKV); prefetch_tmap(&mCtx);
    }
    __syncthreads();
    TS6();
    pdl_launch();
    pdl_wait();
    TS6();
    if (threadIdx.x == 0) { TL_MARK(1); }

    if (warp < 4) {
        reg_dealloc<40>();
        if (warp == 0) {
          if (elect_one()) {
            int ks = 0, kph = 1, vs = 0, vph = 1;
            int head, qt;
            bool have = attn_get_tile(0, head, qt);
            if (have) {
                mbar_expect_tx(qfull, AT_TILE);
                tma_load_3d(sQ, &mQKV, qfull, 0, head * S_LEN + qt * 128, 0);
            }
            for (int t = 0; have; t++) {
                const int krow = (NH + head) * S_LEN, vrow = (2 * NH + head) * S_LEN;
                for (int j = 0; j <= qt + 1; j++) {
                    if (j <= qt) {
                        mbar_wait(kempty + 8 * ks, kph);
                        mbar_expect_tx(kfull + 8 * ks, AT_TILE);
                        tma_load_3d(sK + ks * AT_TILE, &mQKV, kfull + 8 * ks, 0, krow + j * 128, 0);
                        if (++ks == AT_KST) { ks = 0; kph ^= 1; }
                    }
                    if (j > 0) {
                        mbar_wait(vempty + 8 * vs, vph);
                        mbar_expect_tx(vfull + 8 * vs, AT_TILE);
                        tma_load_3d(sV + vs * AT_TILE, &mQKV, vfull + 8 * vs, 0, vrow + (j - 1) * 128, 0);
                        if (++vs == AT_VST) { vs = 0; vph ^= 1; }
                    }
                }
                have = attn_get_tile(t + 1, head, qt);
                if (have) {
                    const int b = (t + 1) & 1, u = (t + 1) >> 1;
                    mbar_wait(qempty + 8 * b, (u & 1) ^ 1);
                    mbar_expect_tx(qfull + 8 * b, AT_TILE);
                    tma_load_3d(sQ + b * AT_TILE, &mQKV, qfull + 8 * b, 0, head * S_LEN + qt * 128, 0);
                }
            }
          }
        } else if (warp == 1) {
            if (elect_one()) {
                int head, qt;
                for (int t = 0; attn_get_tile(t, head, qt); t++) {
                    #pragma unroll
                    for (int w = 0; w < 2; w++) {
                        mbar_wait(ofull + 8 * w, t & 1);
                        fence_proxy_async();
                        const uint32_t src = sO + w * 16384;
                        tma_store_2d(&mCtx, src, head * 128, qt * 128 + w * 64);
                        tma_store_2d(&mCtx, src + 8192, head * 128 + 64, qt * 128 + w * 64);
                        tma_commit();
                    }
                    tma_wait_read<1>(); mbar_arrive(oempty);
                    tma_wait_read<0>(); mbar_arrive(oempty + 8);
                }
                tma_wait<0>();
                TL_END(1);
            }
        } else if (warp == 2) {
            for (int c0 = blockIdx.x * 8; c0 < DM + FF; c0 += gridDim.x * 8) {
                const bool first = c0 < DM;
                const bf16* wp = first ? static_cast<const bf16*>(pf.ptr[1]) + c0 : static_cast<const bf16*>(pf.ptr[3]) + (c0 - DM);
                const int ld = first ? DM : FF;
                float a[8] = {0.f, 0.f, 0.f, 0.f, 0.f, 0.f, 0.f, 0.f};
                #pragma unroll 2
                for (int r = lane; r < DM; r += 32) {
                    float f[8]; unpack8(__ldg(reinterpret_cast<const uint4*>(wp + (size_t)r * ld)), f);
                    #pragma unroll
                    for (int e = 0; e < 8; e++) a[e] += f[e];
                }
                #pragma unroll
                for (int e = 0; e < 8; e++) a[e] = warp_sum(a[e]);
                if (lane == 0) {
                    *reinterpret_cast<float4*>(pf.colsum + c0) = make_float4(a[0], a[1], a[2], a[3]);
                    *reinterpret_cast<float4*>(pf.colsum + c0 + 4) = make_float4(a[4], a[5], a[6], a[7]);
                }
            }
            int head, qt, tp = 0, jp = 0, ahead = 0, wstep = -AT_WPF;
            for (int t = 0; attn_get_tile(t, head, qt); t++) wstep += qt + 1;
            bool have = attn_get_tile(0, head, qt);
            auto next_blk = [&]() { if (++jp > qt) { jp = 0; tp++; have = attn_get_tile(tp, head, qt); } };
            while (have && ahead < AT_PFD) { next_blk(); ahead++; }
            for (int st = 0; have; st++) {
                uint32_t cur, spins = 0;
                do {
                    asm volatile("ld.volatile.shared.u32 %0, [%1];" : "=r"(cur) : "r"(stepctr));
                    if ((int)cur >= st) break;
                    __nanosleep(200);
                } while (++spins < 100000u);
                if (tp >= 2) {
                    if (jp == 0) {
                        const bf16* qp = pf.qkv + ((size_t)head * S_LEN + qt * 128) * HD;
                        #pragma unroll
                        for (int r = 0; r < 8; r++) prefetch_l2(qp + (r * 32 + lane) * 64);
                    }
                    if (qt == 15) {
                        const bf16* kp = pf.qkv + ((size_t)(NH + head) * S_LEN + jp * 128) * HD;
                        const bf16* vp = pf.qkv + ((size_t)(2 * NH + head) * S_LEN + jp * 128) * HD;
                        #pragma unroll
                        for (int r = 0; r < 8; r++) { prefetch_l2(kp + (r * 32 + lane) * 64); prefetch_l2(vp + (r * 32 + lane) * 64); }
                    }
                }
                if (st == wstep) {
                    #pragma unroll 1
                    for (int k = 0; k < 5; k++) {
                        const char* base = reinterpret_cast<const char*>(pf.ptr[k]);
                        for (uint32_t o = (blockIdx.x * 32 + lane) * 128u; o < pf.bytes[k]; o += gridDim.x * 32 * 128u) prefetch_l2(base + o);
                    }
                }
                next_blk();
            }
        } else if (warp == 3) {
            int ks = 0, kph = 0, vs = 0, vph = 0, nstep = 0;
            int head, qt;
            bool have = attn_get_tile(0, head, qt);
            for (int t = 0; have; t++) {
                int nh, nq;
                const bool nxt = attn_get_tile(t + 1, nh, nq);
                const int j0 = (t == 0) ? 0 : 1;
                for (int j = j0; j <= qt + 1; j++) {
                    const bool last = j == qt + 1;
                    if (j == 0) mbar_wait(qfull, 0);
                    if (last && nxt) mbar_wait(qfull + 8 * ((t + 1) & 1), ((t + 1) >> 1) & 1);
                    if (!last || nxt) { mbar_wait(kfull + 8 * ks, kph); if (++ks == AT_KST) { ks = 0; kph ^= 1; } }
                    if (j > 0) { mbar_wait(vfull + 8 * vs, vph); if (++vs == AT_VST) { vs = 0; vph ^= 1; } }
                    bar_sync(1, 288);
                    if (lane == 0) asm volatile("st.volatile.shared.u32 [%0], %1;" :: "r"(stepctr), "r"(++nstep) : "memory");
                    bar_sync(2, 288);
                }
                have = nxt; qt = nq; head = nh;
            }
        }
    } else {
        reg_alloc<232>();
        const int w = (warp >> 2) - 1;
        const int wq = warp & 3;
        const int row0 = w * 64 + wq * 16 + (lane >> 2);
        const int qc = (lane & 3) * 2;
        if (w == 1) bar_arrive(1, 288);
#define ATS()
        float O[64], S[64];
        uint32_t P0[32], P1[32];
        int ks = 0, vs = 0;
        int head, qt;
        float m0 = 0.f, m1 = 0.f, l0 = 0.f, l1 = 0.f;
        bool zm = false;
        const int thr0 = row0 - qc;

        auto mask_diag = [&]() {
            int thr = thr0;
            asm volatile("" : "+r"(thr));
            #pragma unroll
            for (int j = 0; j < 16; j++) {
                if (8 * j > thr) S[4 * j] = -INFINITY;
                if (8 * j + 1 > thr) S[4 * j + 1] = -INFINITY;
                if (8 * j - 8 > thr) S[4 * j + 2] = -INFINITY;
                if (8 * j - 7 > thr) S[4 * j + 3] = -INFINITY;
            }
        };
        auto epilogue = [&](int t, float i0, float i1) {
            const int r = (lane & 7) + ((lane >> 3) & 1) * 8;
            const uint32_t rowaddr = sO + w * 16384 + (wq * 16 + r) * 128;
            mbar_wait(oempty + 8 * w, (t & 1) ^ 1);
            #pragma unroll
            for (int j = 0; j < 16; j += 2) {
                const int cg = j + (lane >> 4);
                const uint32_t a = rowaddr + (cg >> 3) * 8192 + (((cg & 7) ^ (lane & 7)) << 4);
                stmatrix_x4(a, pack_bf16(O[4 * j] * i0, O[4 * j + 1] * i0), pack_bf16(O[4 * j + 2] * i1, O[4 * j + 3] * i1),
                               pack_bf16(O[4 * j + 4] * i0, O[4 * j + 5] * i0), pack_bf16(O[4 * j + 6] * i1, O[4 * j + 7] * i1));
            }
            __syncwarp();
            if (lane == 0) mbar_arrive(ofull + 8 * w);
        };
        const uint32_t sig = (wq == 0 && lane == 0);
        int t = 0, j = 1;
        int nhead = 0, nqt = 0;
        bool have_next = false;
        auto step = [&](uint32_t (&Pin)[32], uint32_t (&Pout)[32]) {
            const bool trans = j > qt;
            const int qb = (t + (trans ? 1 : 0)) & 1;
            ATS();
            bar_sync(1 + w, 288);
            ATS();
            wgmma_fence();
            attn_qk(S, make_desc(sQ + qb * AT_TILE + w * 8192, 16, 1024), make_desc(sK + ks * AT_TILE, 16, 1024));
            wgmma_commit();
            attn_pv(O, Pin, make_desc(sV + vs * AT_TILE, 16384, 1024), j != 1);
            wgmma_commit();
            bar_arrive(1 + (w ^ 1), 288);
            ATS();
            wgmma_wait<1>();
            fence_regs(S);
            ATS();
            const bool diag = trans ? (nqt == 0) : (j == qt);
            mbar_arrive_if(kempty + 8 * ks, sig);
            mbar_arrive_if(qempty + 8 * qb, sig && diag);
            ks ^= 1;
            if (__builtin_expect(diag, 0)) mask_diag();
            float lp0 = l0, lp1 = l1;
            if (__builtin_expect(trans, 0)) {
                zm = attn_first_max(S, m0, m1);
                l0 = 0.f; l1 = 0.f;
            }
            ATS();
            float s0, s1;
            attn_exp_pack(S, m0, m1, zm, Pout, s0, s1);
            const bool bad = __any_sync(0xffffffffu, !(s0 <= AT_BIG && s1 <= AT_BIG));
            ATS();
            if (__builtin_expect(bad, 0)) {
                asm volatile("wgmma.wait_group.sync.aligned 0; // fallback" ::: "memory");
                fence_regs(O);
                float d0, d1;
                attn_rowmax(S, d0, d1);
                d0 = fmaxf(d0, 0.f); d1 = fmaxf(d1, 0.f);
                m0 += d0; m1 += d1; zm = false;
                if (!trans) {
                    const float sc0 = ex2(-d0), sc1 = ex2(-d1);
                    l0 *= sc0; l1 *= sc1;
                    #pragma unroll
                    for (int i = 0; i < 16; i++) {
                        O[4 * i] *= sc0; O[4 * i + 1] *= sc0; O[4 * i + 2] *= sc1; O[4 * i + 3] *= sc1;
                    }
                }
                attn_exp_pack_shift(S, d0, d1, Pout, s0, s1);
            } else {
                asm volatile("wgmma.wait_group.sync.aligned 0; // common" ::: "memory");
            }
            fence_regs(O); fence_regs(Pin);
            mbar_arrive_if(vempty + 8 * vs, sig);
            vs ^= 1;
            l0 += s0; l1 += s1;
            if (__builtin_expect(trans, 0)) {
                epilogue(t, __fdividef(1.f, quad_sum(lp0)), __fdividef(1.f, quad_sum(lp1)));
                t++; head = nhead; qt = nqt; j = 1;
                have_next = attn_get_tile(t + 1, nhead, nqt);
            } else j++;
            ATS();
        };

        auto final_pv = [&](uint32_t (&Pin)[32]) {
            bar_sync(1 + w, 288);
            wgmma_fence();
            attn_pv(O, Pin, make_desc(sV + vs * AT_TILE, 16384, 1024), j != 1);
            wgmma_commit();
            bar_arrive(1 + (w ^ 1), 288);
            const float i0 = __fdividef(1.f, quad_sum(l0)), i1 = __fdividef(1.f, quad_sum(l1));
            wgmma_wait<0>();
            fence_regs(O); fence_regs(Pin);
            epilogue(t, i0, i1);
        };

        if (attn_get_tile(0, head, qt)) {
            have_next = attn_get_tile(1, nhead, nqt);
            TS6();
            bar_sync(1 + w, 288);
            TL_FIRST(1);
            TS6();
            wgmma_fence();
            attn_qk(S, make_desc(sQ + w * 8192, 16, 1024), make_desc(sK + ks * AT_TILE, 16, 1024));
            wgmma_commit();
            bar_arrive(1 + (w ^ 1), 288);
            wgmma_wait<0>();
            fence_regs(S);
            mbar_arrive_if(kempty + 8 * ks, sig);
            mbar_arrive_if(qempty, sig && qt == 0);
            ks ^= 1;
            TS6();
            if (qt == 0) mask_diag();
            zm = attn_first_max(S, m0, m1);
            attn_exp_pack(S, m0, m1, zm, P0, l0, l1);
            TS6();
            while (true) {
                if (j > qt && !have_next) { final_pv(P0); break; }
                step(P0, P1);
                if (j > qt && !have_next) { final_pv(P1); break; }
                step(P1, P0);
            }
        }
    }
}
__device__ __forceinline__ float gelu_tanh(float x) {
    const float u = x * fmaf(x * x, 0.044715f * 0.7978845608028654f, 0.7978845608028654f);
    float t;
    asm("tanh.approx.f32 %0, %1;" : "=f"(t) : "f"(u));
    const float hx = 0.5f * x;
    return fmaf(hx, t, hx);
}
__device__ __forceinline__ float gelu_half(float h) {
    const float u = h * fmaf(h * h, 8.f * 0.044715f * 0.7978845608028654f, 2.f * 0.7978845608028654f);
    float t;
    asm("tanh.approx.f32 %0, %1;" : "=f"(t) : "f"(u));
    return fmaf(h, t, h);
}
__device__ __forceinline__ float bf_lo(uint32_t u) { return __uint_as_float(u << 16); }
__device__ __forceinline__ float bf_hi(uint32_t u) { return __uint_as_float(u & 0xffff0000u); }
__device__ __forceinline__ void cluster_sync_relaxed() {
    asm volatile("barrier.cluster.arrive.relaxed.aligned;" ::: "memory");
    cluster_wait();
}

constexpr int GO_ST = 4;
constexpr int GO_STAGE = 16384 + 32768;
constexpr int GO_SMEM = GO_ST * GO_STAGE + 32768 + 1024 + 256;

__global__ void __cluster_dims__(2, 1, 1) __launch_bounds__(384, 1)
k_oproj(const __grid_constant__ CUtensorMap mCtx, const __grid_constant__ CUtensorMap mWo, const __grid_constant__ CUtensorMap mH) {
    TL_START(2);
    GTS_DECL
    GTS();
    extern __shared__ uint8_t smem_raw[];
    const uint32_t s0 = (smem_u32(smem_raw) + 1023) & ~1023u;
    const uint32_t sStg = s0 + GO_ST * GO_STAGE, full = sStg + 32768, empty = full + 8 * GO_ST;
    const int warp = __shfl_sync(0xffffffffu, threadIdx.x >> 5, 0);
    const int lane = threadIdx.x & 31;
    const uint32_t rank = cluster_ctarank();
    const int cl = blockIdx.x >> 1;
    const int rowblk = (cl >> 3) * 2 + rank, nh = cl & 1, ks = (cl >> 1) & 3;
    if (warp == 0 && elect_one()) {
        for (int i = 0; i < GO_ST; i++) { mbar_init(full + 8 * i, 1); mbar_init(empty + 8 * i, 4); }
        fence_mbar_init();
        fence_proxy_async();
        prefetch_tmap(&mCtx); prefetch_tmap(&mWo); prefetch_tmap(&mH);
    }
    __syncthreads();
    cluster_sync_relaxed();
    pdl_launch();
    if (warp < 4) {
        reg_dealloc<40>();
        if (warp == 0 && elect_one()) {
            for (int kb = 0; kb < GO_ST; kb++) {
                mbar_expect_tx(full + 8 * kb, GO_STAGE);
                tma_load_3d_mc(s0 + kb * GO_STAGE + 16384 + rank * 16384, &mWo, full + 8 * kb, 0, ks * 1024 + kb * 64, nh * 4 + rank * 2, (uint16_t)3);
            }
            pdl_wait();
            if (true) { TL_MARK(2); }
            int s = 0, ph = 1;
            for (int kb = 0; kb < 16; kb++) {
                const int k0 = ks * 1024 + kb * 64;
                const uint32_t st = s0 + s * GO_STAGE;
                if (kb >= GO_ST) {
                    mbar_wait(empty + 8 * s, ph);
                    mbar_expect_tx(full + 8 * s, GO_STAGE);
                    tma_load_3d_mc(st + 16384 + rank * 16384, &mWo, full + 8 * s, 0, k0, nh * 4 + rank * 2, (uint16_t)3);
                }
                tma_load_2d(st, &mCtx, full + 8 * s, k0, rowblk * 128);
                if (++s == GO_ST) { s = 0; ph ^= 1; }
            }
            for (int i = 0; i < GO_ST; i++) { mbar_wait(empty + 8 * s, ph); if (++s == GO_ST) { s = 0; ph ^= 1; } }
        }
    } else {
        reg_alloc<232>();
        const int w = (warp >> 2) - 1, wq = warp & 3;
        float accL[64], accH[64];
        int s = 0, ph = 0;
        for (int kb = 0; kb < 16 - GO_ST; kb++) {
            mbar_wait(full + 8 * s, ph);
            if (kb == 0) { TL_FIRST(2); }
            if (kb == 0 || kb == 8) GTS();
            const uint32_t st = s0 + s * GO_STAGE;
            const uint64_t dA = make_desc(st + w * 8192, 16, 1024), dB = make_desc(st + 16384, 8192, 1024);
            wgmma_fence();
            #pragma unroll
            for (int k = 0; k < 4; k++) {
                wgmma_ss_n128<0, 1>(accL, desc_add(dA, k * 32), desc_add(dB, k * 2048), (kb | k) != 0);
                wgmma_ss_n128<0, 1>(accH, desc_add(dA, k * 32), desc_add(dB, 16384 + k * 2048), (kb | k) != 0);
            }
            wgmma_commit();
            wgmma_wait<1>();
            if (kb > 0) { const int sp = s == 0 ? GO_ST - 1 : s - 1; if (wq < 2 && lane == 0) mbar_arrive_cta(empty + 8 * sp, wq); }
            if (++s == GO_ST) { s = 0; ph ^= 1; }
        }
        {
            int s2 = s, ph2 = ph;
            #pragma unroll
            for (int i = 0; i < GO_ST; i++) {
                mbar_wait(full + 8 * s2, ph2);
                const uint32_t st = s0 + s2 * GO_STAGE;
                const uint64_t dA = make_desc(st + w * 8192, 16, 1024), dB = make_desc(st + 16384, 8192, 1024);
                wgmma_fence();
                #pragma unroll
                for (int k = 0; k < 4; k++) wgmma_ss_n128<0, 1>(accL, desc_add(dA, k * 32), desc_add(dB, k * 2048), 1);
                if (i == 0) {
                    wgmma_commit();
                    wgmma_wait<1>();
                    const int sp = s == 0 ? GO_ST - 1 : s - 1;
                    if (wq < 2 && lane == 0) mbar_arrive_cta(empty + 8 * sp, wq);
                }
                if (++s2 == GO_ST) { s2 = 0; ph2 ^= 1; }
            }
            wgmma_commit();
            s2 = s;
            #pragma unroll
            for (int i = 0; i < GO_ST; i++) {
                const uint32_t st = s0 + s2 * GO_STAGE;
                const uint64_t dA = make_desc(st + w * 8192, 16, 1024), dB = make_desc(st + 16384, 8192, 1024);
                #pragma unroll
                for (int k = 0; k < 4; k++) wgmma_ss_n128<0, 1>(accH, desc_add(dA, k * 32), desc_add(dB, 16384 + k * 2048), 1);
                if (++s2 == GO_ST) s2 = 0;
            }
            wgmma_commit();
        }
        const int r = (lane & 7) + ((lane >> 3) & 1) * 8;
        auto epi = [&](const float (&a)[64], uint32_t stg, int col0) {
            const uint32_t rowa = stg + (wq * 16 + r) * 128;
            #pragma unroll
            for (int j = 0; j < 16; j += 2) {
                const int cg = j + (lane >> 4);
                stmatrix_x4(rowa + (cg >> 3) * 8192 + (((cg & 7) ^ (lane & 7)) << 4),
                    pack_bf16(a[4 * j], a[4 * j + 1]), pack_bf16(a[4 * j + 2], a[4 * j + 3]),
                    pack_bf16(a[4 * j + 4], a[4 * j + 5]), pack_bf16(a[4 * j + 6], a[4 * j + 7]));
            }
            bar_sync(3 + w, 128);
            if (wq == 0 && elect_one()) {
                fence_proxy_async();
                tma_red_add_2d(&mH, stg + (ks & 1) * 8192, col0 + (ks & 1) * 64, rowblk * 128 + w * 64);
                tma_red_add_2d(&mH, stg + ((ks & 1) ^ 1) * 8192, col0 + ((ks & 1) ^ 1) * 64, rowblk * 128 + w * 64);
                tma_commit();
            }
        };
        wgmma_wait<1>();
        fence_regs(accL);
        GTS();
        epi(accL, sStg + w * 16384, nh * 256);
        wgmma_wait<0>();
        fence_regs(accH);
        GTS();
        if (wq < 2 && lane == 0) {
            for (int i = 0; i < GO_ST; i++) mbar_arrive_cta(empty + 8 * i, wq);
        }
        bar_sync(1, 256);
        epi(accH, s0 + w * 16384, nh * 256 + 128);
        GTS();
        if (wq == 0 && elect_one()) { tma_wait<0>(); GTS(); TL_END(2); }
    }
}

constexpr int G1_SMEM = 65536 + 8 * 16384 + 16384 + 1024 + 64 + 512 + 64;

__global__ void __launch_bounds__(384, 1)
k_g1(const __grid_constant__ CUtensorMap mH, const __grid_constant__ CUtensorMap mW1, const __grid_constant__ CUtensorMap mT1,
     float2* __restrict__ stats, const float* __restrict__ cs1, float2* __restrict__ x1stat) {
    TL_START(3);
    GTS_DECL
    GTS();
    extern __shared__ uint8_t smem_raw[];
    const uint32_t sA = (smem_u32(smem_raw) + 1023) & ~1023u;
    const uint32_t sBm = sA + 65536, sStg = sBm + 8 * 16384, full = sStg + 16384, sStat = full + 64;
    const int warp = __shfl_sync(0xffffffffu, threadIdx.x >> 5, 0);
    const int lane = threadIdx.x & 31;
    const int rb = blockIdx.x >> 2, nq = blockIdx.x & 3;
    if (warp == 0 && elect_one()) {
        for (int i = 0; i < 8; i++) mbar_init(full + 8 * i, 1);
        fence_mbar_init();
        fence_proxy_async();
        for (int kb = 0; kb < 8; kb++) {
            mbar_expect_tx(full + 8 * kb, 16384 + 8192);
            tma_load_3d(sBm + kb * 16384, &mW1, full + 8 * kb, 0, kb * 64, nq * 2);
        }
        prefetch_tmap(&mH); prefetch_tmap(&mT1);
    }
    __syncthreads();
    pdl_launch();
    if (warp < 4) {
        if (warp == 0 && elect_one()) {
            pdl_wait();
            if (true) { TL_MARK(3); }
            for (int kb = 0; kb < 8; kb++) tma_load_2d(sA + kb * 8192, &mH, full + 8 * kb, kb * 64, rb * 64);
        }
    } else {
        const int w = (warp >> 2) - 1, wq = warp & 3;
        pdl_wait();
        float cs[16];
        #pragma unroll
        for (int j = 0; j < 8; j++) {
            const float2 t = __ldcg(reinterpret_cast<const float2*>(cs1 + nq * 128 + w * 64 + j * 8 + (lane & 3) * 2));
            cs[2 * j] = t.x; cs[2 * j + 1] = t.y;
        }
        const int srow = (warp - 4) * 8 + (lane >> 2);
        uint32_t soff[2];
        #pragma unroll
        for (int i = 0; i < 2; i++) soff[i] = sA + srow * 128 + ((((lane & 3) * 2 + i) ^ (srow & 7)) << 4);
        float sm0 = 0.f, sm1 = 0.f, sq0 = 0.f, sq1 = 0.f, shift = 0.f;
        float acc[32];
        const uint64_t dA = make_desc(sA, 16, 1024);
        #pragma unroll
        for (int kb = 0; kb < 8; kb++) {
            mbar_wait(full + 8 * kb, 0);
            if (kb == 0) { TL_FIRST(3); }
            if (kb == 0) GTS();
            wgmma_fence();
            const uint64_t dB = make_desc(sBm + kb * 16384 + w * 8192, 8192, 1024);
            #pragma unroll
            for (int k = 0; k < 4; k++) wgmma_ss_n64<0, 1>(acc, desc_add(dA, kb * 8192 + k * 32), desc_add(dB, k * 2048), (kb | k) != 0);
            wgmma_commit();
            const uint4 v0 = lds128(soff[0] + kb * 8192), v1 = lds128(soff[1] + kb * 8192);
            if (kb == 0) shift = __shfl_sync(0xffffffffu, __uint_as_float(v0.x << 16), lane & ~3);
            float f0[8], f1[8]; unpack8(v0, f0); unpack8(v1, f1);
            #pragma unroll
            for (int e = 0; e < 8; e++) {
                const float a = f0[e] - shift, b = f1[e] - shift;
                sm0 += a; sm1 += b; sq0 = fmaf(a, a, sq0); sq1 = fmaf(b, b, sq1);
            }
        }
        {
            float sm = sm0 + sm1, sq = sq0 + sq1;
            sm += __shfl_xor_sync(0xffffffffu, sm, 1); sq += __shfl_xor_sync(0xffffffffu, sq, 1);
            sm += __shfl_xor_sync(0xffffffffu, sm, 2); sq += __shfl_xor_sync(0xffffffffu, sq, 2);
            const float dm = sm * (1.f / DM);
            const float var = fmaxf(sq * (1.f / DM) - dm * dm, 0.f), mean = dm + shift;
            const float rstd = rsqrtf(var + LN_EPS);
            const float sc = 0.5f * rstd * rsqrtf(var * rstd * rstd + LN_EPS);
            if ((lane & 3) == 0) {
                asm volatile("st.shared.v2.f32 [%0], {%1, %2};" :: "r"(sStat + srow * 8), "f"(mean), "f"(sc) : "memory");
                if (nq == 0) { stats[rb * 64 + srow] = make_float2(mean, rstd); x1stat[rb * 64 + srow] = make_float2(0.f, 0.f); }
            }
        }
        bar_sync(1, 256);
        float mean0, sc0, mean1, sc1;
        asm volatile("ld.shared.v2.f32 {%0, %1}, [%2];" : "=f"(mean0), "=f"(sc0) : "r"(sStat + (wq * 16 + (lane >> 2)) * 8));
        asm volatile("ld.shared.v2.f32 {%0, %1}, [%2];" : "=f"(mean1), "=f"(sc1) : "r"(sStat + (wq * 16 + (lane >> 2) + 8) * 8));
        wgmma_wait<0>();
        fence_regs(acc);
        GTS();
        #pragma unroll
        for (int j = 0; j < 8; j++) {
            acc[4 * j]     = gelu_half(fmaf(-mean0, cs[2 * j],     acc[4 * j])     * sc0);
            acc[4 * j + 1] = gelu_half(fmaf(-mean0, cs[2 * j + 1], acc[4 * j + 1]) * sc0);
            acc[4 * j + 2] = gelu_half(fmaf(-mean1, cs[2 * j],     acc[4 * j + 2]) * sc1);
            acc[4 * j + 3] = gelu_half(fmaf(-mean1, cs[2 * j + 1], acc[4 * j + 3]) * sc1);
        }
        const int r = (lane & 7) + ((lane >> 3) & 1) * 8;
        const uint32_t rowa = sStg + w * 8192 + (wq * 16 + r) * 128;
        #pragma unroll
        for (int j = 0; j < 8; j += 2) {
            const int cg = j + (lane >> 4);
            stmatrix_x4(rowa + ((cg ^ (lane & 7)) << 4),
                pack_bf16(acc[4 * j], acc[4 * j + 1]), pack_bf16(acc[4 * j + 2], acc[4 * j + 3]),
                pack_bf16(acc[4 * j + 4], acc[4 * j + 5]), pack_bf16(acc[4 * j + 6], acc[4 * j + 7]));
        }
        bar_sync(3 + w, 128);
        if (wq == 0 && elect_one()) {
            fence_proxy_async();
            tma_store_2d(&mT1, sStg + w * 8192, nq * 128 + w * 64, rb * 64);
            tma_commit();
            GTS();
            tma_wait<0>();
            GTS();
            TL_END(3);
        }
    }
}

constexpr int GS_ST = 4;
constexpr int GS_STAGE = 32768 + 16384;
constexpr int GS_SMEM = GS_ST * GS_STAGE + 16384 + 1024 + 256;

template<int MODE>
__global__ void __cluster_dims__(2, 1, 1) __launch_bounds__(384, 1)
k_gs(const __grid_constant__ CUtensorMap mA, const __grid_constant__ CUtensorMap mW, const __grid_constant__ CUtensorMap mOut,
     const __grid_constant__ CUtensorMap mBase,
     const bf16* __restrict__ h, const float2* __restrict__ stats, const bf16* __restrict__ x1, float2* __restrict__ x1stat) {
    TL_START((MODE == 0 ? 4 : 6));
    GTS_DECL
    GTS();
    constexpr int NKB = MODE == 0 ? 4 : FF / 128;
    extern __shared__ uint8_t smem_raw[];
    const uint32_t s0 = (smem_u32(smem_raw) + 1023) & ~1023u;
    const uint32_t sStg = s0 + GS_ST * GS_STAGE, full = sStg + 16384, empty = full + 8 * GS_ST;
    const int warp = __shfl_sync(0xffffffffu, threadIdx.x >> 5, 0);
    const int lane = threadIdx.x & 31;
    const uint32_t rank = cluster_ctarank();
    const int rb = blockIdx.x >> 3, nt = blockIdx.x & 7;
    if (warp == 0 && elect_one()) {
        for (int i = 0; i < GS_ST; i++) { mbar_init(full + 8 * i, 1); mbar_init(empty + 8 * i, 4); }
        fence_mbar_init();
        fence_proxy_async();
        for (int kb = 0; kb < GS_ST; kb++) {
            mbar_expect_tx(full + 8 * kb, GS_STAGE);
            tma_load_2d(s0 + kb * GS_STAGE + 32768, &mW, full + 8 * kb, nt * 64, kb * 128);
        }
        prefetch_tmap(&mA); prefetch_tmap(&mOut);
    }
    __syncthreads();
    cluster_sync_relaxed();
    pdl_launch();
    if (warp < 4) {
        if (warp == 0 && elect_one()) {
            pdl_wait();
            if (true) { TL_MARK((MODE == 0 ? 4 : 6)); }
            int s = 0, ph = 1;
            for (int kb = 0; kb < NKB; kb++) {
                const uint32_t st = s0 + s * GS_STAGE;
                if (kb >= GS_ST) {
                    mbar_wait(empty + 8 * s, ph);
                    mbar_expect_tx(full + 8 * s, GS_STAGE);
                    tma_load_2d(st + 32768, &mW, full + 8 * s, nt * 64, kb * 128);
                }
                const int shift = MODE == 0 ? (kb == 0 ? -1 : (kb == 1 ? 1 : (kb == 2 ? -2 : 2))) : 0;
                tma_load_3d_mc(st + rank * 16384, &mA, full + 8 * s, 0, rb * 128 + rank * 64 + shift, kb * 2, (uint16_t)3);
                if (++s == GS_ST) { s = 0; ph ^= 1; }
            }
            if (NKB > GS_ST) for (int i = 0; i < GS_ST; i++) { mbar_wait(empty + 8 * s, ph); if (++s == GS_ST) { s = 0; ph ^= 1; } }
        }
    } else {
        const int w = (warp >> 2) - 1, wq = warp & 3;
        const int row0 = rb * 128 + w * 64 + wq * 16 + (lane >> 2), col0 = nt * 64 + (lane & 3) * 2;
        uint32_t ra[16], rb2[16];
        float2 st0, st1;
        float acc[32];
        int s = 0, ph = 0;
        auto kstep = [&](int kb) {
            mbar_wait(full + 8 * s, ph);
            if (kb == 0) { TL_FIRST((MODE == 0 ? 4 : 6)); }
            if (kb == 0) GTS();
            const uint32_t st = s0 + s * GS_STAGE;
            const uint64_t dA = make_desc(st + w * 16384, 16, 1024), dB = make_desc(st + 32768, 8192, 1024);
            wgmma_fence();
            #pragma unroll
            for (int k = 0; k < 8; k++)
                wgmma_ss_n64<0, 1>(acc, desc_add(dA, (k >> 2) * 8192 + (k & 3) * 32), desc_add(dB, k * 2048), (kb | k) != 0);
            wgmma_commit();
            if (NKB > GS_ST) {
                wgmma_wait<1>();
                if (kb > 0) { const int sp = s == 0 ? GS_ST - 1 : s - 1; if (wq < 2 && lane == 0) mbar_arrive_cta(empty + 8 * sp, wq); }
            }
            if (++s == GS_ST) { s = 0; ph ^= 1; }
        };
        #pragma unroll
        for (int kb = 0; kb < 4; kb++) {
            kstep(kb);
            #pragma unroll
            for (int j = 2 * kb; j < 2 * kb + 2; j++) {
                ra[2 * j] = __ldcg(reinterpret_cast<const uint32_t*>(h + (size_t)row0 * DM + col0 + j * 8));
                ra[2 * j + 1] = __ldcg(reinterpret_cast<const uint32_t*>(h + (size_t)(row0 + 8) * DM + col0 + j * 8));
                if (MODE == 1) {
                    rb2[2 * j] = __ldcg(reinterpret_cast<const uint32_t*>(x1 + (size_t)row0 * DM + col0 + j * 8));
                    rb2[2 * j + 1] = __ldcg(reinterpret_cast<const uint32_t*>(x1 + (size_t)(row0 + 8) * DM + col0 + j * 8));
                }
            }
            if (MODE == 0 && kb == 0) { st0 = __ldcg(stats + row0); st1 = __ldcg(stats + row0 + 8); }
        }
        for (int kb = 4; kb < NKB; kb++) kstep(kb);
        wgmma_wait<0>();
        fence_regs(acc);
        GTS();
        if (NKB > GS_ST) { const int sp = s == 0 ? GS_ST - 1 : s - 1; if (wq < 2 && lane == 0) mbar_arrive_cta(empty + 8 * sp, wq); }
        #pragma unroll
        for (int j = 0; j < 8; j++) {
            float r0 = bf_lo(ra[2 * j]), r1 = bf_hi(ra[2 * j]), r2 = bf_lo(ra[2 * j + 1]), r3 = bf_hi(ra[2 * j + 1]);
            if (MODE == 0) {
                r0 = (r0 - st0.x) * st0.y; r1 = (r1 - st0.x) * st0.y; r2 = (r2 - st1.x) * st1.y; r3 = (r3 - st1.x) * st1.y;
            } else {
                r0 += bf_lo(rb2[2 * j]); r1 += bf_hi(rb2[2 * j]); r2 += bf_lo(rb2[2 * j + 1]); r3 += bf_hi(rb2[2 * j + 1]);
            }
            acc[4 * j] += r0; acc[4 * j + 1] += r1; acc[4 * j + 2] += r2; acc[4 * j + 3] += r3;
        }
        const int r = (lane & 7) + ((lane >> 3) & 1) * 8;
        const uint32_t rowa = sStg + w * 8192 + (wq * 16 + r) * 128;
        #pragma unroll
        for (int j = 0; j < 8; j += 2) {
            const int cg = j + (lane >> 4);
            stmatrix_x4(rowa + ((cg ^ (lane & 7)) << 4),
                pack_bf16(acc[4 * j], acc[4 * j + 1]), pack_bf16(acc[4 * j + 2], acc[4 * j + 3]),
                pack_bf16(acc[4 * j + 4], acc[4 * j + 5]), pack_bf16(acc[4 * j + 6], acc[4 * j + 7]));
        }
        if (MODE == 0) {
            bar_sync(1, 256);
            const uint32_t rowb = s0 + w * 8192 + (wq * 16 + r) * 128;
            #pragma unroll
            for (int j = 0; j < 8; j += 2) {
                const int cg = j + (lane >> 4);
                stmatrix_x4(rowb + ((cg ^ (lane & 7)) << 4),
                    pack_bf16(acc[4 * j] + bf_lo(ra[2 * j]), acc[4 * j + 1] + bf_hi(ra[2 * j])),
                    pack_bf16(acc[4 * j + 2] + bf_lo(ra[2 * j + 1]), acc[4 * j + 3] + bf_hi(ra[2 * j + 1])),
                    pack_bf16(acc[4 * j + 4] + bf_lo(ra[2 * j + 2]), acc[4 * j + 5] + bf_hi(ra[2 * j + 2])),
                    pack_bf16(acc[4 * j + 6] + bf_lo(ra[2 * j + 3]), acc[4 * j + 7] + bf_hi(ra[2 * j + 3])));
            }
            float a0 = 0.f, q0 = 0.f, a1 = 0.f, q1 = 0.f;
            #pragma unroll
            for (int j = 0; j < 8; j++) {
                a0 += acc[4 * j] + acc[4 * j + 1]; q0 = fmaf(acc[4 * j], acc[4 * j], fmaf(acc[4 * j + 1], acc[4 * j + 1], q0));
                a1 += acc[4 * j + 2] + acc[4 * j + 3]; q1 = fmaf(acc[4 * j + 2], acc[4 * j + 2], fmaf(acc[4 * j + 3], acc[4 * j + 3], q1));
            }
            a0 = quad_sum(a0); q0 = quad_sum(q0); a1 = quad_sum(a1); q1 = quad_sum(q1);
            if ((lane & 3) == 0) {
                atomicAdd(&x1stat[row0].x, a0); atomicAdd(&x1stat[row0].y, q0);
                atomicAdd(&x1stat[row0 + 8].x, a1); atomicAdd(&x1stat[row0 + 8].y, q1);
            }
        }
        bar_sync(3 + w, 128);
        if (wq == 0 && elect_one()) {
            fence_proxy_async();
            tma_store_2d(&mOut, sStg + w * 8192, nt * 64, rb * 128 + w * 64);
            if (MODE == 0) tma_store_2d(&mBase, s0 + w * 8192, nt * 64, rb * 128 + w * 64);
            tma_commit();
            GTS();
            tma_wait<0>();
            GTS();
            TL_END((MODE == 0 ? 4 : 6));
        }
        if (MODE == 0) {
        }
    }
}

constexpr int ML_ST = 4;
constexpr int ML_SMEM = 131072 + ML_ST * 16384 + 32768 + 1024 + 256 + 896
;

__global__ void __cluster_dims__(2, 1, 1) __launch_bounds__(384, 1)
k_mlp(const __grid_constant__ CUtensorMap mX1, const __grid_constant__ CUtensorMap mW3, const __grid_constant__ CUtensorMap mW4,
      bf16* __restrict__ out, const float* __restrict__ cs3, const float2* __restrict__ x1stat) {
    TL_START(5);
    GTS_DECL
    GTS();
    extern __shared__ uint8_t smem_raw[];
    const uint32_t sA = (smem_u32(smem_raw) + 1023) & ~1023u;
    const uint32_t sBst = sA + 131072, sU = sBst + ML_ST * 16384, full = sU + 32768, empty = full + 8 * ML_ST, afull = empty + 8 * ML_ST, rfull = afull + 64, rempty = rfull + 32, sCs = rempty + 32;
    const int warp = __shfl_sync(0xffffffffu, threadIdx.x >> 5, 0);
    const int lane = threadIdx.x & 31;
    const uint32_t rank = cluster_ctarank();
    const int cl = blockIdx.x >> 1;
    const int rb = (cl >> 3) * 2 + rank, nt = cl & 7;
    const int ncol = nt * 224;
    if (warp == 0 && elect_one()) {
        for (int i = 0; i < ML_ST; i++) { mbar_init(full + 8 * i, 1); mbar_init(empty + 8 * i, 4); }
        for (int i = 0; i < 8; i++) mbar_init(afull + 8 * i, 1);
        for (int i = 0; i < 4; i++) { mbar_init(rfull + 8 * i, 4); mbar_init(rempty + 8 * i, 1); }
        fence_mbar_init();
        fence_proxy_async();
        prefetch_tmap(&mX1); prefetch_tmap(&mW3); prefetch_tmap(&mW4);
    }
    __syncthreads();
    cluster_sync_relaxed();
    pdl_launch();
    if (warp < 4) {
        reg_dealloc<40>();
        if (warp == 0 && elect_one()) {
            auto load_w = [&](int i, int s) {
                mbar_expect_tx(full + 8 * s, 16384);
                const uint32_t dst = sBst + s * 16384 + rank * 8192;
                if (i < 16) tma_load_2d_mc(dst, &mW3, full + 8 * s, ncol + (i >> 3) * 128 + rank * 64, (i & 7) * 64, (uint16_t)3);
                else        tma_load_2d_mc(dst, &mW4, full + 8 * s, ((i - 16) >> 2) * 128 + rank * 64, ncol + (i & 3) * 64, (uint16_t)3);
            };
            for (int i = 0; i < ML_ST; i++) load_w(i, i);
            pdl_wait();
            if (true) { TL_MARK(5); }
            auto load_a = [&](int c) {
                mbar_expect_tx(afull + 8 * c, 16384);
                tma_load_2d(sA + c * 16384, &mX1, afull + 8 * c, c * 64, rb * 128);
            };
            for (int c = 0; c < 4; c++) load_a(c);
            int s = 0, ph = 0;
            for (int i = ML_ST; i < 32; i++) {
                mbar_wait(empty + 8 * s, ph);
                load_w(i, s);
                if (i < 8) load_a(i);
                if (++s == ML_ST) { s = 0; ph ^= 1; }
            }
            for (int i = 0; i < ML_ST; i++) { mbar_wait(empty + 8 * s, ph); if (++s == ML_ST) { s = 0; ph ^= 1; } }
        } else if (warp == 1 || warp == 2) {
            const int w = warp - 1;
            #pragma unroll 1
            for (int t = 0; t < 4; t++) {
                const int b = t & 1;
                mbar_wait(rfull + 8 * (2 * w + b), t >> 1);
                const uint32_t stg = sA + 32768 + b * 32768 + w * 16384;
                bf16* dst = out + (size_t)(rb * 128 + w * 64 + (lane >> 3)) * DM + t * 128 + (lane & 7) * 8;
                #pragma unroll 4
                for (int it = 0; it < 32; it++) {
                    const int c = (it + nt * 4) & 31;
                    const int row = (c & 15) * 4 + (lane >> 3), ch = c >> 4;
                    const uint4 v = lds128(stg + ch * 8192 + row * 128 + (((lane & 7) ^ (row & 7)) << 4));
                    asm volatile("red.global.add.noftz.v4.bf16x2 [%0], {%1, %2, %3, %4};"
                        :: "l"(dst + (size_t)((c & 15) * 4) * DM + ch * 64), "r"(v.x), "r"(v.y), "r"(v.z), "r"(v.w) : "memory");
                }
                __syncwarp();
                if (lane == 0) mbar_arrive(rempty + 8 * (2 * w + b));
            }
            TL_END(5);
        }
    } else {
        reg_alloc<232>();
        const int w = (warp >> 2) - 1, wq = warp & 3;
#define STS_TS()
        float sc0, sc1, mean0, mean1;
        pdl_wait();
        {
            const int ct = threadIdx.x - 128;
            if (ct < 224) { const float v = __ldcg(cs3 + ncol + ct); asm volatile("st.shared.f32 [%0], %1;" :: "r"(sCs + 4 * ct), "f"(v) : "memory"); }
            const int row0 = rb * 128 + w * 64 + wq * 16 + (lane >> 2);
            const float2 s0 = __ldcg(x1stat + row0), s1 = __ldcg(x1stat + row0 + 8);
            mean0 = s0.x * (1.f / DM); mean1 = s1.x * (1.f / DM);
            sc0 = 0.5f * rsqrtf(fmaxf(s0.y * (1.f / DM) - mean0 * mean0, 0.f) + LN_EPS);
            sc1 = 0.5f * rsqrtf(fmaxf(s1.y * (1.f / DM) - mean1 * mean1, 0.f) + LN_EPS);
            bar_sync(1, 256);
        }
        int s = 0, ph = 0;
        const int r = (lane & 7) + ((lane >> 3) & 1) * 8;
        const uint32_t rowoff = w * 8192 + (wq * 16 + r) * 128;
        auto release = [&](int stage) { if (wq < 2 && lane == 0) mbar_arrive_cta(empty + 8 * stage, wq); };
        auto advance = [&]() { if (++s == ML_ST) { s = 0; ph ^= 1; } };
        float accA[64], accB[64];
        const uint64_t dU01 = make_desc(sU + w * 8192, 16, 1024), dU23 = make_desc(sA + w * 8192, 16, 1024);
        auto mma2 = [&](float (&cur)[64], int kb) {
            STS_TS();
            mbar_wait(full + 8 * s, ph);
            STS_TS();
            const uint64_t dB = make_desc(sBst + s * 16384, 8192, 1024);
            const uint64_t dU = desc_add(kb < 2 ? dU01 : dU23, (kb & 1) * 16384);
            wgmma_fence();
            #pragma unroll
            for (int k = 0; k < (kb == 3 ? 2 : 4); k++)
                wgmma_ss_n128<0, 1>(cur, desc_add(dU, k * 32), desc_add(dB, k * 2048), (kb | k) != 0);
            wgmma_commit();
            advance();
        };
        auto prev_stage = [&](int back) { int q = s - back; return q < 0 ? q + ML_ST : q; };
        {
            float acc1[48];
            float (&acc0)[64] = accB;
            const uint64_t dA = make_desc(sA + w * 8192, 16, 1024);
            const uint32_t csa = sCs + (lane & 3) * 8;
            auto ldcs = [&](int col) { float2 v; asm volatile("ld.shared.v2.f32 {%0, %1}, [%2];" : "=f"(v.x), "=f"(v.y) : "r"(csa + col * 4)); return v; };
            auto act = [&](const float* a, int col, uint32_t dst, int cg) {
                const float2 c0 = ldcs(col), c1 = ldcs(col + 8);
                stmatrix_x4(dst + rowoff + (((cg & 7) ^ (lane & 7)) << 4),
                    pack_bf16(gelu_half(fmaf(-mean0, c0.x, a[0]) * sc0), gelu_half(fmaf(-mean0, c0.y, a[1]) * sc0)),
                    pack_bf16(gelu_half(fmaf(-mean1, c0.x, a[2]) * sc1), gelu_half(fmaf(-mean1, c0.y, a[3]) * sc1)),
                    pack_bf16(gelu_half(fmaf(-mean0, c1.x, a[4]) * sc0), gelu_half(fmaf(-mean0, c1.y, a[5]) * sc0)),
                    pack_bf16(gelu_half(fmaf(-mean1, c1.x, a[6]) * sc1), gelu_half(fmaf(-mean1, c1.y, a[7]) * sc1)));
            };
            #pragma unroll
            for (int i = 0; i < 16; i++) {
                const int t = i >> 3, kb = i & 7;
                STS_TS();
                if (t == 0) mbar_wait(afull + 8 * kb, 0);
                mbar_wait(full + 8 * s, ph);
                STS_TS();
                if (i == 0) { TL_FIRST(5); GTS(); }
                const uint64_t dB = make_desc(sBst + s * 16384, 8192, 1024);
                wgmma_fence();
                #pragma unroll
                for (int k = 0; k < 4; k++) {
                    if (t == 0) wgmma_ss_n128<0, 1>(acc0, desc_add(dA, kb * 16384 + k * 32), desc_add(dB, k * 2048), (kb | k) != 0);
                    else        wgmma_ss_n96<0, 1>(acc1, desc_add(dA, kb * 16384 + k * 32), desc_add(dB, k * 2048), (kb | k) != 0);
                }
                wgmma_commit();
                wgmma_wait<1>();
                STS_TS();
                if (i > 0) release(s == 0 ? ML_ST - 1 : s - 1);
                advance();
                if (t == 1) {
                    if (kb == 0) fence_regs(acc0);
                    const int cg = 2 * kb + (lane >> 4);
                    act(&acc0[8 * kb], 16 * kb, sU + (kb >> 2) * 16384, cg);
                }
            }
            wgmma_wait<0>();
            fence_regs(acc1);
            release(prev_stage(1));
            GTS();
            fence_proxy_async();
            bar_sync(3 + w, 128);
            mma2(accA, 0); mma2(accA, 1);
            #pragma unroll
            for (int j = 0; j < 6; j++) {
                const int cg = 2 * j + (lane >> 4);
                act(&acc1[8 * j], 128 + 16 * j, sA + (j >> 2) * 16384, cg);
            }
            fence_proxy_async();
            bar_sync(3 + w, 128);
            GTS();
        }
        {
            auto epi_slices = [&](const float (&a)[64], int t, int j0, int j1) {
                const uint32_t stg = sA + 32768 + (t & 1) * 32768 + w * 16384 + (wq * 16 + r) * 128;
                #pragma unroll
                for (int j2 = j0; j2 < j1; j2++) {
                    const int j = 2 * j2, cg = j + (lane >> 4);
                    stmatrix_x4(stg + (cg >> 3) * 8192 + (((cg & 7) ^ (lane & 7)) << 4),
                        pack_bf16(a[4 * j], a[4 * j + 1]), pack_bf16(a[4 * j + 2], a[4 * j + 3]),
                        pack_bf16(a[4 * j + 4], a[4 * j + 5]), pack_bf16(a[4 * j + 6], a[4 * j + 7]));
                }
            };
            auto epi_issue = [&](int t) {
                __syncwarp();
                if (lane == 0) mbar_arrive(rfull + 8 * (2 * w + (t & 1)));
            };
            wgmma_wait<0>();
            release(prev_stage(2)); release(prev_stage(1));
            mma2(accA, 2); mma2(accA, 3);
            auto next_tile = [&](float (&cur)[64], float (&prev)[64], int t) {
                mma2(cur, 0);
                wgmma_wait<1>();
                fence_regs(prev);
                release(prev_stage(3)); release(prev_stage(2));
                mma2(cur, 1);
                if (t == 3) mbar_wait(rempty + 8 * (2 * w), 0);
                epi_slices(prev, t - 1, 0, 8);
                epi_issue(t - 1);
                wgmma_wait<0>();
                release(prev_stage(2)); release(prev_stage(1));
                mma2(cur, 2); mma2(cur, 3);
            };
            next_tile(accB, accA, 1);
            next_tile(accA, accB, 2);
            next_tile(accB, accA, 3);
            wgmma_wait<0>();
            fence_regs(accB);
            release(prev_stage(2)); release(prev_stage(1));
            GTS();
            mbar_wait(rempty + 8 * (2 * w + 1), 0);
            epi_slices(accB, 3, 0, 8);
            epi_issue(3);
            GTS();
        }
    }
}
__device__ __align__(1024) bf16  g_qkv[3 * NH * S_LEN * HD];
__device__ __align__(1024) bf16  g_ctx[S_LEN * NH * HD];
__device__ __align__(1024) bf16  g_h[S_LEN * DM];
__device__ __align__(1024) float2 g_stats[S_LEN];
__device__ __align__(1024) float g_colsum[DM + FF];
__device__ __align__(1024) float2 g_x1stat[S_LEN];
__device__ __align__(1024) bf16  g_t1[S_LEN * DM];
__device__ __align__(1024) bf16  g_x1[S_LEN * DM];

typedef CUresult (*EncodeTiledFn)(CUtensorMap*, CUtensorMapDataType, cuuint32_t, void*, const cuuint64_t*, const cuuint64_t*,
                                  const cuuint32_t*, const cuuint32_t*, CUtensorMapInterleave, CUtensorMapSwizzle,
                                  CUtensorMapL2promotion, CUtensorMapFloatOOBfill);
static EncodeTiledFn g_encode = nullptr;

static CUtensorMap make_map(const void* ptr, int rank, const uint64_t* dims, const uint64_t* strides, const uint32_t* box,
                            CUtensorMapSwizzle sw = CU_TENSOR_MAP_SWIZZLE_128B) {
    const CUtensorMapDataType dt = CU_TENSOR_MAP_DATA_TYPE_BFLOAT16;
    CUtensorMap m;
    cuuint64_t d[3], st[2]; cuuint32_t b[3], es[3] = {1, 1, 1};
    for (int i = 0; i < rank; i++) { d[i] = dims[i]; b[i] = box[i]; }
    for (int i = 0; i < rank - 1; i++) st[i] = strides[i];
    g_encode(&m, dt, rank, (void*)ptr, d, st, b, es, CU_TENSOR_MAP_INTERLEAVE_NONE, sw,
             CU_TENSOR_MAP_L2_PROMOTION_L2_256B, CU_TENSOR_MAP_FLOAT_OOB_FILL_NONE);
    return m;
}
static CUtensorMap map2d(const void* p, uint64_t cols, uint64_t rows, uint32_t box_cols, uint32_t box_rows) {
    uint64_t d[2] = {cols, rows}, s[1] = {cols * 2}; uint32_t b[2] = {box_cols, box_rows};
    return make_map(p, 2, d, s, b);
}
static CUtensorMap map3d(const void* p, uint64_t cols, uint64_t rows, uint32_t box_rows, uint32_t nchunks) {
    uint64_t d[3] = {64, rows, cols / 64}, s[2] = {cols * 2, 128}; uint32_t b[3] = {64, box_rows, nchunks};
    return make_map(p, 3, d, s, b);
}

template<typename... KArgs, typename... Args>
static void launch(void (*kern)(KArgs...), int grid, int smem, cudaStream_t st, bool pdl, Args... args) {
    cudaLaunchConfig_t cfg = {};
    cfg.gridDim = dim3(grid); cfg.blockDim = dim3(384); cfg.dynamicSmemBytes = smem; cfg.stream = st;
    cudaLaunchAttribute at[1];
    at[0].id = cudaLaunchAttributeProgrammaticStreamSerialization;
    at[0].val.programmaticStreamSerializationAllowed = 1;
    cfg.attrs = at; cfg.numAttrs = pdl ? 1 : 0;
    cudaLaunchKernelEx(&cfg, kern, KArgs(args)...);
}

#define USE_PDL 1

struct Plan {
    CUtensorMap mX, mC, mWq, mWk, mWv, mQkvOut, mQkvIn, mCtxOut, mCtxIn, mWo, mH, mW1, mT1out, mT1in, mW2, mX1out, mX1in, mW3, mW4, mOut;
    bf16 *qkv, *ctx, *t1, *x1, *h, *out; float2 *stats, *x1stat; float* colsum;
    AttnSched sched; int attn_grid;
};

static void build_sched(Plan& p, int sms) {
    AttnSched& sc = p.sched;
    for (int i = 0; i < 160; i++) { sc.e[i].x = 0; sc.e[i].y = 0; }
    auto add = [&](int b, int h, int q) {
        const int n = (int)(sc.e[b].y >> 48);
        const unsigned long long v = (unsigned long long)(h * 16 + q);
        if (n < 4) sc.e[b].x |= v << (16 * n); else sc.e[b].y |= v << (16 * (n - 4));
        sc.e[b].y += 1ull << 48;
    };
#define SCHED_MODE 1
    if (sms == 132 && SCHED_MODE == 1) {
        p.attn_grid = 132;
        int b = 0;
        for (int h = 0; h < 8; h++) for (int i = 0; i < 8; i++) { add(b, h, 15 - i); add(b, h, i); b++; }
        for (int h = 8; h < 16; h++) { add(b++, h, 15); for (int i = 0; i < 7; i++) { add(b, h, 14 - i); add(b, h, i); b++; } }
        for (int h = 8; h < 16; h += 2) { add(b, h, 7); add(b, h + 1, 7); b++; }
        b = 64; int r = 0;
        for (int h = 16; h < 25; h++) for (int i = 0; i < 8; i++) {
            if (i == 0 && h < 20) { add(r++, h, 15); continue; }
            add(b, h, 15 - i); add(b, h, i); b++;
        }
        for (int h = 25; h < 32; h++) { add(r++, h, 15); for (int i = 0; i < 7; i++) { add(r, h, 14 - i); add(r, h, i); r++; } }
        for (int h = 25; h < 31; h += 2) { add(r, h, 7); add(r, h + 1, 7); r++; }
        add(r, 31, 7); for (int h = 16; h < 20; h++) add(r, h, 0);
    } else {
        p.attn_grid = sms < 86 ? 86 : (sms > 160 ? 160 : sms);
        for (int q = 0; q < NH * 8; q++) { const int b = q % p.attn_grid; add(b, q >> 3, 15 - (q & 7)); add(b, q >> 3, q & 7); }
    }
}

static void build_plan(Plan& p, void* const* d_in, void* d_out) {
    if (!g_encode) {
        void* fn = nullptr; cudaDriverEntryPointQueryResult qr;
        cudaGetDriverEntryPoint("cuTensorMapEncodeTiled", &fn, cudaEnableDefault, &qr);
        g_encode = (EncodeTiledFn)fn;
        cudaFuncSetAttribute(k_qkv, cudaFuncAttributeMaxDynamicSharedMemorySize, QK_SMEM);
        cudaFuncSetAttribute(k_attn, cudaFuncAttributeMaxDynamicSharedMemorySize, AT_SMEM);
        cudaFuncSetAttribute(k_oproj, cudaFuncAttributeMaxDynamicSharedMemorySize, GO_SMEM);
        cudaFuncSetAttribute(k_g1, cudaFuncAttributeMaxDynamicSharedMemorySize, G1_SMEM);
        cudaFuncSetAttribute(k_gs<0>, cudaFuncAttributeMaxDynamicSharedMemorySize, GS_SMEM);
        cudaFuncSetAttribute(k_mlp, cudaFuncAttributeMaxDynamicSharedMemorySize, ML_SMEM);
    }
    { int dev = 0, sms = 132; cudaGetDevice(&dev); cudaDeviceGetAttribute(&sms, cudaDevAttrMultiProcessorCount, dev); build_sched(p, sms); }
    cudaGetSymbolAddress((void**)&p.qkv, g_qkv); cudaGetSymbolAddress((void**)&p.ctx, g_ctx);
    cudaGetSymbolAddress((void**)&p.h, g_h); cudaGetSymbolAddress((void**)&p.stats, g_stats); cudaGetSymbolAddress((void**)&p.colsum, g_colsum); cudaGetSymbolAddress((void**)&p.x1stat, g_x1stat);
    cudaGetSymbolAddress((void**)&p.t1, g_t1); cudaGetSymbolAddress((void**)&p.x1, g_x1);
    p.mX = map2d(d_in[0], DM, S_LEN, 64, 128);
    p.mC = map2d(d_in[1], DM, S_LEN, 64, 128);
    p.mWq = map2d(d_in[2], NH * HD, DM, 64, 64);
    p.mWk = map2d(d_in[3], NH * HD, DM, 64, 64);
    p.mWv = map2d(d_in[4], NH * HD, DM, 64, 64);
    p.mQkvOut = map2d(p.qkv, HD, 3 * NH * S_LEN, 64, 64);
    p.mQkvIn = map3d(p.qkv, HD, 3 * NH * S_LEN, 128, 2);
    p.mCtxOut = map2d(p.ctx, NH * HD, S_LEN, 64, 64);
    p.mCtxIn = map2d(p.ctx, NH * HD, S_LEN, 64, 128);
    p.mWo = map3d(d_in[5], DM, NH * HD, 64, 2);
    p.mH = map2d(p.h, DM, S_LEN, 64, 64);
    p.mW1 = map3d(d_in[7], DM, DM, 64, 2);
    p.mT1out = map2d(p.t1, DM, S_LEN, 64, 64);
    p.mT1in = map3d(p.t1, DM, S_LEN, 64, 2);
    p.mW2 = map2d(d_in[8], DM, DM, 64, 128);
    p.mX1out = map2d(p.x1, DM, S_LEN, 64, 64);
    p.mX1in = map2d(p.x1, DM, S_LEN, 64, 128);
    p.mW3 = map2d(d_in[9], FF, DM, 64, 64);
    p.mW4 = map2d(d_in[10], DM, FF, 64, 64);
    p.mOut = map2d(d_out, DM, S_LEN, 64, 64);
    p.out = (bf16*)d_out;
}

static void run_stage(const Plan& p, int stage, void* const* d_in, cudaStream_t st, bool pdl) {
    switch (stage) {
    case 0: launch(k_qkv, 128, QK_SMEM, st, false, p.mX, p.mC, p.mWq, p.mWk, p.mWv, p.mQkvOut, (const bf16*)d_in[0], p.h, (const bf16*)d_in[2], (const bf16*)d_in[3], (const bf16*)d_in[4]); break;
    case 1: {
        PrefetchList pf;
        pf.ptr[0] = d_in[5]; pf.bytes[0] = NH * HD * DM * 2;
        pf.ptr[1] = d_in[7]; pf.bytes[1] = DM * DM * 2;
        pf.ptr[2] = d_in[8]; pf.bytes[2] = DM * DM * 2;
        pf.ptr[3] = d_in[9]; pf.bytes[3] = DM * FF * 2;
        pf.ptr[4] = d_in[10]; pf.bytes[4] = DM * FF * 2;
        pf.colsum = p.colsum; pf.qkv = p.qkv;
        launch(k_attn, p.attn_grid, AT_SMEM, st, pdl, p.mQkvIn, p.mCtxOut, pf, p.sched); break; }
    case 2: launch(k_oproj, 128, GO_SMEM, st, pdl, p.mCtxIn, p.mWo, p.mH); break;
    case 3: launch(k_g1, 128, G1_SMEM, st, pdl, p.mH, p.mW1, p.mT1out, p.stats, (const float*)p.colsum, p.x1stat); break;
    case 4: launch(k_gs<0>, 128, GS_SMEM, st, pdl, p.mT1in, p.mW2, p.mX1out, p.mOut, (const bf16*)p.h, (const float2*)p.stats, (const bf16*)nullptr, p.x1stat); break;
    case 5: launch(k_mlp, 128, ML_SMEM, st, pdl, p.mX1in, p.mW3, p.mW4, p.out, (const float*)(p.colsum + DM), (const float2*)p.x1stat); break;
    }
}

constexpr int NUM_STAGES = 6;
extern "C" void kernel_launch(void* const* d_in, const int* in_sizes, int n_in, void* d_out, int out_size) {
    Plan p;
    build_plan(p, d_in, d_out);
    cudaStream_t st = cudaStreamPerThread;
    for (int s = 0; s < NUM_STAGES; s++) run_stage(p, s, d_in, st, USE_PDL);
}
```

```cpp
#include <cuda_runtime.h>
#include <cuda_bf16.h>
#include <cuda.h>
#include <stdint.h>

typedef __nv_bfloat16 bf16;

constexpr int S_LEN = 2048;
constexpr int DM    = 512;
constexpr int NH    = 32;
constexpr int HD    = 128;
constexpr int FF    = 1792;
constexpr float LN_EPS = 1e-5f;
constexpr float AT_SCALE = 0.08838834764831845f * 1.4426950408889634f;

#define SPIN_LIMIT (1u << 20)

__device__ __forceinline__ uint32_t smem_u32(const void* p) { return (uint32_t)__cvta_generic_to_shared(p); }
__device__ __forceinline__ uint32_t elect_one() {
    uint32_t pred;
    asm volatile("{\n.reg .pred px;\nelect.sync _|px, 0xFFFFFFFF;\nselp.u32 %0, 1, 0, px;\n}\n" : "=r"(pred));
    return pred;
}
__device__ __forceinline__ void mbar_init(uint32_t bar, uint32_t count) {
    asm volatile("mbarrier.init.shared::cta.b64 [%0], %1;" :: "r"(bar), "r"(count) : "memory");
}
__device__ __forceinline__ void mbar_expect_tx(uint32_t bar, uint32_t bytes) {
    asm volatile("mbarrier.arrive.expect_tx.shared::cta.b64 _, [%0], %1;" :: "r"(bar), "r"(bytes) : "memory");
}
__device__ __forceinline__ void mbar_arrive(uint32_t bar) {
    asm volatile("mbarrier.arrive.shared::cta.b64 _, [%0];" :: "r"(bar) : "memory");
}
__device__ __forceinline__ void mbar_arrive_if(uint32_t bar, uint32_t flag) {
    asm volatile("{\n.reg .pred p;\nsetp.ne.b32 p, %1, 0;\n@p mbarrier.arrive.shared::cta.b64 _, [%0];\n}" :: "r"(bar), "r"(flag) : "memory");
}
__device__ __forceinline__ void mbar_arrive_cta(uint32_t bar, uint32_t cta) {
    asm volatile("{\n.reg .b32 ra;\nmapa.shared::cluster.u32 ra, %0, %1;\n"
                 "mbarrier.arrive.shared::cluster.b64 _, [ra];\n}" :: "r"(bar), "r"(cta) : "memory");
}
__device__ __forceinline__ bool mbar_try_wait(uint32_t bar, uint32_t parity) {
    uint32_t ok;
    asm volatile("{\n.reg .pred p;\nmbarrier.try_wait.parity.shared::cta.b64 p, [%1], %2;\nselp.u32 %0, 1, 0, p;\n}"
                 : "=r"(ok) : "r"(bar), "r"(parity) : "memory");
    return ok;
}
__device__ __forceinline__ void mbar_wait(uint32_t bar, uint32_t parity) {
    uint32_t n = 0;
    while (!mbar_try_wait(bar, parity) && ++n < SPIN_LIMIT) { }
}
__device__ __forceinline__ void fence_mbar_init() { asm volatile("fence.mbarrier_init.release.cluster;" ::: "memory"); }
__device__ __forceinline__ void fence_proxy_async() { asm volatile("fence.proxy.async.shared::cta;" ::: "memory"); }

__device__ __forceinline__ void tma_load_2d(uint32_t dst, const CUtensorMap* map, uint32_t bar, int c0, int c1) {
    asm volatile("cp.async.bulk.tensor.2d.shared::cluster.global.mbarrier::complete_tx::bytes [%0], [%1, {%3, %4}], [%2];"
        :: "r"(dst), "l"(map), "r"(bar), "r"(c0), "r"(c1) : "memory");
}
__device__ __forceinline__ void tma_load_3d(uint32_t dst, const CUtensorMap* map, uint32_t bar, int c0, int c1, int c2) {
    asm volatile("cp.async.bulk.tensor.3d.shared::cluster.global.mbarrier::complete_tx::bytes [%0], [%1, {%3, %4, %5}], [%2];"
        :: "r"(dst), "l"(map), "r"(bar), "r"(c0), "r"(c1), "r"(c2) : "memory");
}
__device__ __forceinline__ void tma_load_2d_mc(uint32_t dst, const CUtensorMap* map, uint32_t bar, int c0, int c1, uint16_t mask) {
    asm volatile("cp.async.bulk.tensor.2d.shared::cluster.global.mbarrier::complete_tx::bytes.multicast::cluster [%0], [%1, {%3, %4}], [%2], %5;"
        :: "r"(dst), "l"(map), "r"(bar), "r"(c0), "r"(c1), "h"(mask) : "memory");
}
__device__ __forceinline__ void tma_load_3d_mc(uint32_t dst, const CUtensorMap* map, uint32_t bar, int c0, int c1, int c2, uint16_t mask) {
    asm volatile("cp.async.bulk.tensor.3d.shared::cluster.global.mbarrier::complete_tx::bytes.multicast::cluster [%0], [%1, {%3, %4, %5}], [%2], %6;"
        :: "r"(dst), "l"(map), "r"(bar), "r"(c0), "r"(c1), "r"(c2), "h"(mask) : "memory");
}
__device__ __forceinline__ void tma_store_2d(const CUtensorMap* map, uint32_t src, int c0, int c1) {
    asm volatile("cp.async.bulk.tensor.2d.global.shared::cta.bulk_group [%0, {%2, %3}], [%1];"
        :: "l"(map), "r"(src), "r"(c0), "r"(c1) : "memory");
}
__device__ __forceinline__ void tma_red_add_2d(const CUtensorMap* map, uint32_t src, int c0, int c1) {
    asm volatile("cp.reduce.async.bulk.tensor.2d.global.shared::cta.add.bulk_group [%0, {%2, %3}], [%1];"
        :: "l"(map), "r"(src), "r"(c0), "r"(c1) : "memory");
}
__device__ __forceinline__ void prefetch_l2(const void* p) { asm volatile("prefetch.global.L2 [%0];" :: "l"(p)); }
__device__ __forceinline__ void tma_commit() { asm volatile("cp.async.bulk.commit_group;" ::: "memory"); }
template<int N> __device__ __forceinline__ void tma_wait_read() { asm volatile("cp.async.bulk.wait_group.read %0;" :: "n"(N) : "memory"); }
__device__ __forceinline__ void prefetch_tmap(const CUtensorMap* map) {
    asm volatile("prefetch.tensormap [%0];" :: "l"(map) : "memory");
}

__device__ __forceinline__ void wgmma_fence() { asm volatile("wgmma.fence.sync.aligned;" ::: "memory"); }
__device__ __forceinline__ void wgmma_commit() { asm volatile("wgmma.commit_group.sync.aligned;" ::: "memory"); }
template<int N> __device__ __forceinline__ void wgmma_wait() { asm volatile("wgmma.wait_group.sync.aligned %0;" :: "n"(N) : "memory"); }

template<int N> __device__ __forceinline__ void fence_regs(float (&d)[N]) {
    #pragma unroll
    for (int i = 0; i < N; i++) asm volatile("" : "+f"(d[i]) :: "memory");
}
template<int N> __device__ __forceinline__ void fence_regs(uint32_t (&d)[N]) {
    #pragma unroll
    for (int i = 0; i < N; i++) asm volatile("" : "+r"(d[i]) :: "memory");
}

__device__ __forceinline__ uint64_t make_desc(uint32_t addr, uint32_t lbo_bytes, uint32_t sbo_bytes) {
    uint64_t d = 0;
    d |= (uint64_t)((addr & 0x3FFFF) >> 4);
    d |= (uint64_t)((lbo_bytes & 0x3FFFF) >> 4) << 16;
    d |= (uint64_t)((sbo_bytes & 0x3FFFF) >> 4) << 32;
    d |= (uint64_t)1 << 62;
    return d;
}
__device__ __forceinline__ uint64_t desc_add(uint64_t d, uint32_t bytes) {
    return d + (uint64_t)(bytes >> 4);
}

__device__ __forceinline__ void bar_sync(int id, int n) { asm volatile("bar.sync %0, %1;" :: "r"(id), "r"(n) : "memory"); }
__device__ __forceinline__ void bar_arrive(int id, int n) { asm volatile("bar.arrive %0, %1;" :: "r"(id), "r"(n) : "memory"); }
template<int R> __device__ __forceinline__ void reg_alloc() { asm volatile("setmaxnreg.inc.sync.aligned.u32 %0;" :: "n"(R)); }
template<int R> __device__ __forceinline__ void reg_dealloc() { asm volatile("setmaxnreg.dec.sync.aligned.u32 %0;" :: "n"(R)); }
__device__ __forceinline__ uint32_t cluster_ctarank() { uint32_t r; asm volatile("mov.u32 %0, %%cluster_ctarank;" : "=r"(r)); return r; }
__device__ __forceinline__ void cluster_wait() { asm volatile("barrier.cluster.wait.acquire.aligned;" ::: "memory"); }
__device__ __forceinline__ void pdl_wait() { asm volatile("griddepcontrol.wait;" ::: "memory"); }
__device__ __forceinline__ void pdl_launch() { asm volatile("griddepcontrol.launch_dependents;" ::: "memory"); }

__device__ __forceinline__ uint32_t pack_bf16(float lo, float hi) {
    uint32_t r;
    asm("cvt.rn.bf16x2.f32 %0, %1, %2;" : "=r"(r) : "f"(hi), "f"(lo));
    return r;
}
__device__ __forceinline__ float ex2(float x) {
    float y;
    asm("ex2.approx.ftz.f32 %0, %1;" : "=f"(y) : "f"(x));
    return y;
}
__device__ __forceinline__ void stmatrix_x4(uint32_t addr, uint32_t r0, uint32_t r1, uint32_t r2, uint32_t r3) {
    asm volatile("stmatrix.sync.aligned.m8n8.x4.shared.b16 [%0], {%1, %2, %3, %4};"
        :: "r"(addr), "r"(r0), "r"(r1), "r"(r2), "r"(r3) : "memory");
}
template<int TA, int TB> __device__ __forceinline__ void wgmma_ss_n128(float (&d)[64], uint64_t descA, uint64_t descB, int scaleD) {
    asm volatile("{\n.reg .pred p;\n"
        "setp.ne.b32 p, %66, 0;\n"
        "wgmma.mma_async.sync.aligned.m64n128k16.f32.bf16.bf16 "
        "{%0,%1,%2,%3,%4,%5,%6,%7,%8,%9,%10,%11,%12,%13,%14,%15,%16,%17,%18,%19,%20,%21,%22,%23,%24,%25,%26,%27,%28,%29,%30,%31,%32,%33,%34,%35,%36,%37,%38,%39,%40,%41,%42,%43,%44,%45,%46,%47,%48,%49,%50,%51,%52,%53,%54,%55,%56,%57,%58,%59,%60,%61,%62,%63}, "
        "%64, %65, p, 1, 1, %67, %68;\n}\n"
        : "+f"(d[0]),"+f"(d[1]),"+f"(d[2]),"+f"(d[3]),"+f"(d[4]),"+f"(d[5]),"+f"(d[6]),"+f"(d[7]),"+f"(d[8]),"+f"(d[9]),"+f"(d[10]),"+f"(d[11]),"+f"(d[12]),"+f"(d[13]),"+f"(d[14]),"+f"(d[15]),"+f"(d[16]),"+f"(d[17]),"+f"(d[18]),"+f"(d[19]),"+f"(d[20]),"+f"(d[21]),"+f"(d[22]),"+f"(d[23]),"+f"(d[24]),"+f"(d[25]),"+f"(d[26]),"+f"(d[27]),"+f"(d[28]),"+f"(d[29]),"+f"(d[30]),"+f"(d[31]),"+f"(d[32]),"+f"(d[33]),"+f"(d[34]),"+f"(d[35]),"+f"(d[36]),"+f"(d[37]),"+f"(d[38]),"+f"(d[39]),"+f"(d[40]),"+f"(d[41]),"+f"(d[42]),"+f"(d[43]),"+f"(d[44]),"+f"(d[45]),"+f"(d[46]),"+f"(d[47]),"+f"(d[48]),"+f"(d[49]),"+f"(d[50]),"+f"(d[51]),"+f"(d[52]),"+f"(d[53]),"+f"(d[54]),"+f"(d[55]),"+f"(d[56]),"+f"(d[57]),"+f"(d[58]),"+f"(d[59]),"+f"(d[60]),"+f"(d[61]),"+f"(d[62]),"+f"(d[63])
        : "l"(descA), "l"(descB), "r"(scaleD), "n"(TA), "n"(TB));
}
template<int TB> __device__ __forceinline__ void wgmma_rs_n128(float (&d)[64], uint32_t a0, uint32_t a1, uint32_t a2, uint32_t a3, uint64_t descB, int scaleD) {
    asm volatile("{\n.reg .pred p;\n"
        "setp.ne.b32 p, %69, 0;\n"
        "wgmma.mma_async.sync.aligned.m64n128k16.f32.bf16.bf16 "
        "{%0,%1,%2,%3,%4,%5,%6,%7,%8,%9,%10,%11,%12,%13,%14,%15,%16,%17,%18,%19,%20,%21,%22,%23,%24,%25,%26,%27,%28,%29,%30,%31,%32,%33,%34,%35,%36,%37,%38,%39,%40,%41,%42,%43,%44,%45,%46,%47,%48,%49,%50,%51,%52,%53,%54,%55,%56,%57,%58,%59,%60,%61,%62,%63}, "
        "{%64,%65,%66,%67}, %68, p, 1, 1, %70;\n}\n"
        : "+f"(d[0]),"+f"(d[1]),"+f"(d[2]),"+f"(d[3]),"+f"(d[4]),"+f"(d[5]),"+f"(d[6]),"+f"(d[7]),"+f"(d[8]),"+f"(d[9]),"+f"(d[10]),"+f"(d[11]),"+f"(d[12]),"+f"(d[13]),"+f"(d[14]),"+f"(d[15]),"+f"(d[16]),"+f"(d[17]),"+f"(d[18]),"+f"(d[19]),"+f"(d[20]),"+f"(d[21]),"+f"(d[22]),"+f"(d[23]),"+f"(d[24]),"+f"(d[25]),"+f"(d[26]),"+f"(d[27]),"+f"(d[28]),"+f"(d[29]),"+f"(d[30]),"+f"(d[31]),"+f"(d[32]),"+f"(d[33]),"+f"(d[34]),"+f"(d[35]),"+f"(d[36]),"+f"(d[37]),"+f"(d[38]),"+f"(d[39]),"+f"(d[40]),"+f"(d[41]),"+f"(d[42]),"+f"(d[43]),"+f"(d[44]),"+f"(d[45]),"+f"(d[46]),"+f"(d[47]),"+f"(d[48]),"+f"(d[49]),"+f"(d[50]),"+f"(d[51]),"+f"(d[52]),"+f"(d[53]),"+f"(d[54]),"+f"(d[55]),"+f"(d[56]),"+f"(d[57]),"+f"(d[58]),"+f"(d[59]),"+f"(d[60]),"+f"(d[61]),"+f"(d[62]),"+f"(d[63])
        : "r"(a0), "r"(a1), "r"(a2), "r"(a3), "l"(descB), "r"(scaleD), "n"(TB));
}
template<int TA, int TB> __device__ __forceinline__ void wgmma_ss_n64(float (&d)[32], uint64_t descA, uint64_t descB, int scaleD) {
    asm volatile("{\n.reg .pred p;\n"
        "setp.ne.b32 p, %34, 0;\n"
        "wgmma.mma_async.sync.aligned.m64n64k16.f32.bf16.bf16 "
        "{%0,%1,%2,%3,%4,%5,%6,%7,%8,%9,%10,%11,%12,%13,%14,%15,%16,%17,%18,%19,%20,%21,%22,%23,%24,%25,%26,%27,%28,%29,%30,%31}, "
        "%32, %33, p, 1, 1, %35, %36;\n}\n"
        : "+f"(d[0]),"+f"(d[1]),"+f"(d[2]),"+f"(d[3]),"+f"(d[4]),"+f"(d[5]),"+f"(d[6]),"+f"(d[7]),"+f"(d[8]),"+f"(d[9]),"+f"(d[10]),"+f"(d[11]),"+f"(d[12]),"+f"(d[13]),"+f"(d[14]),"+f"(d[15]),"+f"(d[16]),"+f"(d[17]),"+f"(d[18]),"+f"(d[19]),"+f"(d[20]),"+f"(d[21]),"+f"(d[22]),"+f"(d[23]),"+f"(d[24]),"+f"(d[25]),"+f"(d[26]),"+f"(d[27]),"+f"(d[28]),"+f"(d[29]),"+f"(d[30]),"+f"(d[31])
        : "l"(descA), "l"(descB), "r"(scaleD), "n"(TA), "n"(TB));
}
template<int TA, int TB> __device__ __forceinline__ void wgmma_ss_n96(float (&d)[48], uint64_t descA, uint64_t descB, int scaleD) {
    asm volatile("{\n.reg .pred p;\n"
        "setp.ne.b32 p, %50, 0;\n"
        "wgmma.mma_async.sync.aligned.m64n96k16.f32.bf16.bf16 "
        "{%0,%1,%2,%3,%4,%5,%6,%7,%8,%9,%10,%11,%12,%13,%14,%15,%16,%17,%18,%19,%20,%21,%22,%23,%24,%25,%26,%27,%28,%29,%30,%31,%32,%33,%34,%35,%36,%37,%38,%39,%40,%41,%42,%43,%44,%45,%46,%47}, "
        "%48, %49, p, 1, 1, %51, %52;\n}\n"
        : "+f"(d[0]),"+f"(d[1]),"+f"(d[2]),"+f"(d[3]),"+f"(d[4]),"+f"(d[5]),"+f"(d[6]),"+f"(d[7]),"+f"(d[8]),"+f"(d[9]),"+f"(d[10]),"+f"(d[11]),"+f"(d[12]),"+f"(d[13]),"+f"(d[14]),"+f"(d[15]),"+f"(d[16]),"+f"(d[17]),"+f"(d[18]),"+f"(d[19]),"+f"(d[20]),"+f"(d[21]),"+f"(d[22]),"+f"(d[23]),"+f"(d[24]),"+f"(d[25]),"+f"(d[26]),"+f"(d[27]),"+f"(d[28]),"+f"(d[29]),"+f"(d[30]),"+f"(d[31]),"+f"(d[32]),"+f"(d[33]),"+f"(d[34]),"+f"(d[35]),"+f"(d[36]),"+f"(d[37]),"+f"(d[38]),"+f"(d[39]),"+f"(d[40]),"+f"(d[41]),"+f"(d[42]),"+f"(d[43]),"+f"(d[44]),"+f"(d[45]),"+f"(d[46]),"+f"(d[47])
        : "l"(descA), "l"(descB), "r"(scaleD), "n"(TA), "n"(TB));
}
constexpr int QK_PF = 2;
constexpr int QK_ST = 5;
constexpr int QK_A_BYTES = 128 * 512 * 2;
constexpr int QK_B_BYTES = 64 * 128 * 2;
constexpr int QK_STG = 2 * 64 * 64 * 2;
constexpr int QK_SMEM = QK_A_BYTES + QK_ST * QK_B_BYTES + QK_STG + 1024 + 256;

__device__ __forceinline__ void unpack8(const uint4& v, float (&f)[8]) {
    const uint32_t u[4] = {v.x, v.y, v.z, v.w};
    #pragma unroll
    for (int i = 0; i < 4; i++) { f[2 * i] = __uint_as_float(u[i] << 16); f[2 * i + 1] = __uint_as_float(u[i] & 0xffff0000u); }
}
__device__ __forceinline__ float warp_sum(float v) {
    #pragma unroll
    for (int o = 16; o > 0; o >>= 1) v += __shfl_xor_sync(0xffffffffu, v, o);
    return v;
}
__device__ __forceinline__ uint4 lds128(uint32_t a) {
    uint4 v; asm volatile("ld.shared.v4.u32 {%0,%1,%2,%3}, [%4];" : "=r"(v.x), "=r"(v.y), "=r"(v.z), "=r"(v.w) : "r"(a)); return v;
}
__device__ __forceinline__ void sts128(uint32_t a, const uint4& v) {
    asm volatile("st.shared.v4.u32 [%0], {%1,%2,%3,%4};" :: "r"(a), "r"(v.x), "r"(v.y), "r"(v.z), "r"(v.w) : "memory");
}

__device__ __forceinline__ void ln_rows_inplace(uint32_t sA, int row_base, int lane, uint32_t afull, int nbar, int aph) {
    const int row = row_base + (lane >> 1);
    const uint32_t rowa = sA + row * 128;
    uint32_t off[4];
    #pragma unroll
    for (int i = 0; i < 4; i++) off[i] = rowa + ((((lane & 1) * 4 + i) ^ (row & 7)) << 4);
    float sm0 = 0.f, sm1 = 0.f, sq0 = 0.f, sq1 = 0.f, shift = 0.f;
    #pragma unroll 1
    for (int c = 0; c < 8; c++) {
        if (c < nbar) mbar_wait(afull + 8 * c, aph);
        uint4 v[4];
        #pragma unroll
        for (int i = 0; i < 4; i++) v[i] = lds128(off[i] + c * 16384);
        if (c == 0) shift = __shfl_sync(0xffffffffu, __uint_as_float(v[0].x << 16), lane & ~1);
        #pragma unroll
        for (int i = 0; i < 4; i++) {
            float f[8]; unpack8(v[i], f);
            #pragma unroll
            for (int e = 0; e < 8; e += 2) {
                const float a = f[e] - shift, b = f[e + 1] - shift;
                sm0 += a; sm1 += b; sq0 = fmaf(a, a, sq0); sq1 = fmaf(b, b, sq1);
            }
        }
    }
    float sm = sm0 + sm1, sq = sq0 + sq1;
    sm += __shfl_xor_sync(0xffffffffu, sm, 1); sq += __shfl_xor_sync(0xffffffffu, sq, 1);
    const float dm = sm * (1.f / DM);
    const float var = fmaxf(sq * (1.f / DM) - dm * dm, 0.f);
    const float rs = rsqrtf(var + LN_EPS), nb = -(dm + shift) * rs;
    #pragma unroll 2
    for (int c = 0; c < 8; c++) {
        uint4 v[4];
        #pragma unroll
        for (int i = 0; i < 4; i++) v[i] = lds128(off[i] + c * 16384);
        #pragma unroll
        for (int i = 0; i < 4; i++) {
            float f[8]; unpack8(v[i], f);
            uint4 o;
            o.x = pack_bf16(fmaf(f[0], rs, nb), fmaf(f[1], rs, nb)); o.y = pack_bf16(fmaf(f[2], rs, nb), fmaf(f[3], rs, nb));
            o.z = pack_bf16(fmaf(f[4], rs, nb), fmaf(f[5], rs, nb)); o.w = pack_bf16(fmaf(f[6], rs, nb), fmaf(f[7], rs, nb));
            sts128(off[i] + c * 16384, o);
        }
    }
}

__device__ __forceinline__ int qkv_tile_count(int g) { return g < 2 ? 11 : (g == 2 ? 10 : (g < 7 ? 13 : 12)); }
__device__ __forceinline__ int qkv_tile_id(int g, int i) {
    if (g < 3) return 31 - (3 * i + g);
    const int idx = 5 * i + (g - 3);
    return 32 * (1 + (idx & 1)) + 31 - (idx >> 1);
}
struct QkvCtx {
    uint32_t sA, sBst, sStg, full, empty, sfull, sempty;
    int s, ph;
    int sph;
    int w, wq, lane;
    float osc;
};

__device__ __forceinline__ void qkv_epi_slice(const float (&acc)[64], int j2, uint32_t stg_row, int lane, float sc) {
    const int j = 2 * j2;
    const int cg = (j & 7) + (lane >> 4);
    stmatrix_x4(stg_row + ((cg ^ (lane & 7)) << 4),
                pack_bf16(acc[4 * j] * sc, acc[4 * j + 1] * sc), pack_bf16(acc[4 * j + 2] * sc, acc[4 * j + 3] * sc),
                pack_bf16(acc[4 * j + 4] * sc, acc[4 * j + 5] * sc), pack_bf16(acc[4 * j + 6] * sc, acc[4 * j + 7] * sc));
}
__device__ __forceinline__ void qkv_stg_acquire(QkvCtx& c) { mbar_wait(c.sempty + 8 * c.w, c.sph ^ 1); }
__device__ __forceinline__ void qkv_stg_publish(QkvCtx& c) {
    __syncwarp();
    if (c.lane == 0) mbar_arrive(c.sfull + 8 * c.w);
    c.sph ^= 1;
}
__device__ __forceinline__ void qkv_release(const QkvCtx& c, int stage) {
    if (c.wq < 2 && c.lane == 0) mbar_arrive_cta(c.empty + 8 * stage, c.wq);
}

template<bool WAIT_A, bool HAS_PREV, int W>
__device__ __forceinline__ void qkv_tile(QkvCtx& c, float (&cur)[64], float (&prev)[64], uint32_t afull, int aph) {
    const uint64_t dA = make_desc(c.sA + c.w * 8192, 16, 1024);
    const int r = (c.lane & 7) + ((c.lane >> 3) & 1) * 8;
    const uint32_t stg_row = c.sStg + c.w * 8192 + (c.wq * 16 + r) * 128;
    #pragma unroll
    for (int kb = 0; kb < 8; kb++) {
        if (WAIT_A) mbar_wait(afull + 8 * kb, aph);
        mbar_wait(c.full + 8 * c.s, c.ph);
        const uint64_t dB = make_desc(c.sBst + c.s * QK_B_BYTES, 8192, 1024);
        wgmma_fence();
        #pragma unroll
        for (int k = 0; k < 4; k++)
            wgmma_ss_n128<0, 1>(cur, desc_add(dA, kb * 16384 + k * 32), desc_add(dB, k * 2048), (kb | k) != 0);
        wgmma_commit();
        const int scur = c.s;
        const int sprev = c.s == 0 ? QK_ST - 1 : c.s - 1;
        if (++c.s == QK_ST) { c.s = 0; c.ph ^= 1; }
        if (kb > 0) { wgmma_wait<1>(); qkv_release(c, sprev); }
        if (HAS_PREV) {
            const int e = kb - 2 * W;
            if (e == 0 || e == 4) qkv_stg_acquire(c);
            if (e == 0 || e == 1 || e == 4 || e == 5) {
                const int j2 = (e >> 2) * 4 + (e & 1) * 2;
                qkv_epi_slice(prev, j2, stg_row, c.lane, c.osc); qkv_epi_slice(prev, j2 + 1, stg_row, c.lane, c.osc);
            }
            if (e == 1 || e == 5) qkv_stg_publish(c);
        }
        if (kb == 7) {
            wgmma_wait<0>();
            fence_regs(cur);
            qkv_release(c, scur);
        }
    }
}
__device__ __forceinline__ void qkv_drain(QkvCtx& c, float (&acc)[64]) {
    const int r = (c.lane & 7) + ((c.lane >> 3) & 1) * 8;
    const uint32_t stg_row = c.sStg + c.w * 8192 + (c.wq * 16 + r) * 128;
    #pragma unroll
    for (int h = 0; h < 2; h++) {
        qkv_stg_acquire(c);
        #pragma unroll
        for (int j = 0; j < 4; j++) qkv_epi_slice(acc, 4 * h + j, stg_row, c.lane, c.osc);
        qkv_stg_publish(c);
    }
}

__global__ void __cluster_dims__(2, 1, 1) __launch_bounds__(384, 1)
k_qkv(const __grid_constant__ CUtensorMap mX, const __grid_constant__ CUtensorMap mC,
      const __grid_constant__ CUtensorMap mWq, const __grid_constant__ CUtensorMap mWk,
      const __grid_constant__ CUtensorMap mWv, const __grid_constant__ CUtensorMap mOut,
      const bf16* __restrict__ x, bf16* __restrict__ hacc,
      const bf16* __restrict__ wq, const bf16* __restrict__ wk, const bf16* __restrict__ wv) {
    extern __shared__ uint8_t smem_raw[];
    const uint32_t sA = (smem_u32(smem_raw) + 1023) & ~1023u;
    const uint32_t sBst = sA + QK_A_BYTES, sStg = sBst + QK_ST * QK_B_BYTES, sB = sStg + QK_STG;
    const uint32_t full = sB, empty = full + 8 * QK_ST, afull = empty + 8 * QK_ST,
                   sfull = afull + 64, sempty = sfull + 16;
    const int warp = __shfl_sync(0xffffffffu, threadIdx.x >> 5, 0);
    const int lane = threadIdx.x & 31;
    const uint32_t rank = cluster_ctarank();
    const int cl = blockIdx.x >> 1;
    const int rowblk = (cl >> 3) * 2 + rank;
    const int g = cl & 7;
    const int ntile = qkv_tile_count(g);
    if (warp == 0 && elect_one()) {
        for (int i = 0; i < QK_ST; i++) { mbar_init(full + 8 * i, 1); mbar_init(empty + 8 * i, 4); }
        for (int i = 0; i < 8; i++) mbar_init(afull + 8 * i, 1);
        for (int i = 0; i < 2; i++) { mbar_init(sfull + 8 * i, 4); mbar_init(sempty + 8 * i, 1); }
        fence_mbar_init();
        fence_proxy_async();
        const CUtensorMap* mA = (g < 3) ? &mX : &mC;
        const int n_early = (g < 3) ? 8 : 2;
        for (int kb = 0; kb < n_early; kb++) {
            mbar_expect_tx(afull + 8 * kb, 16384);
            tma_load_2d(sA + kb * 16384, mA, afull + 8 * kb, kb * 64, rowblk * 128);
        }
    }
    __syncthreads();
    asm volatile("barrier.cluster.arrive.relaxed.aligned;" ::: "memory");
    cluster_wait();
    pdl_launch();

    if (warp < 4) {
        reg_dealloc<40>();
        if (warp == 0) {
            if (elect_one()) {
                int s = 0, ph = 1;
                for (int i = 0; i < ntile; i++) {
                    const int n = qkv_tile_id(g, i);
                    const CUtensorMap* mW = n < 32 ? &mWq : (n < 64 ? &mWk : &mWv);
                    const int col = (n & 31) * 128 + rank * 64;
                    for (int kb = 0; kb < 8; kb++) {
                        mbar_wait(empty + 8 * s, ph);
                        mbar_expect_tx(full + 8 * s, QK_B_BYTES);
                        tma_load_2d_mc(sBst + s * QK_B_BYTES + rank * 8192, mW, full + 8 * s, col, kb * 64, (uint16_t)3);
                        if (++s == QK_ST) { s = 0; ph ^= 1; }
                        if (i == 0 && g >= 3 && kb < 6) {
                            mbar_expect_tx(afull + 8 * (kb + 2), 16384);
                            tma_load_2d(sA + (kb + 2) * 16384, &mC, afull + 8 * (kb + 2), (kb + 2) * 64, rowblk * 128);
                        }
                    }
                }
                for (int i = 0; i < QK_ST; i++) { mbar_wait(empty + 8 * s, ph); if (++s == QK_ST) { s = 0; ph ^= 1; } }
            }
        } else if (warp < 3) {
            const int w = warp - 1;
            const bool leader = elect_one();
            for (int i = 0; i < 2 * ntile; i++) {
                if (leader) {
                    mbar_wait(sfull + 8 * w, i & 1);
                    fence_proxy_async();
                    tma_store_2d(&mOut, sStg + w * 8192, (i & 1) * 64, qkv_tile_id(g, i >> 1) * S_LEN + rowblk * 128 + w * 64);
                    tma_commit();
                }
                __syncwarp();
                const int ip = (i >> 1) + QK_PF + 1;
                if ((i & 1) == 0 && ip < ntile) {
                    const int np = qkv_tile_id(g, ip);
                    prefetch_l2((np < 32 ? wq : (np < 64 ? wk : wv)) + (size_t)((cl >> 3) * 64 + w * 32 + lane) * (NH * HD) + (np & 31) * 128 + rank * 64);
                }
                if (leader) {
                    tma_wait_read<0>();
                    mbar_arrive(sempty + 8 * w);
                }
            }
            if (leader) { tma_wait_read<0>(); }
        } else {
            mbar_wait(afull + 8 * 7, 0);
            for (int i = 1; i < QK_PF + 1; i++) {
                const int np = qkv_tile_id(g, i);
                const bf16* wp = (np < 32 ? wq : (np < 64 ? wk : wv)) + (size_t)((cl >> 3) * 64 + lane) * (NH * HD) + (np & 31) * 128 + rank * 64;
                prefetch_l2(wp); prefetch_l2(wp + 32 * (NH * HD));
            }
            const uint4* xs = reinterpret_cast<const uint4*>(x + (size_t)blockIdx.x * 16 * DM);
            uint4* hd = reinterpret_cast<uint4*>(hacc + (size_t)blockIdx.x * 16 * DM);
            #pragma unroll 4
            for (int i = lane; i < 16 * DM / 8; i += 32) hd[i] = __ldg(xs + i);
        }
    } else {
        reg_alloc<232>();
        QkvCtx c;
        c.sA = sA; c.sBst = sBst; c.sStg = sStg; c.full = full; c.empty = empty; c.sfull = sfull; c.sempty = sempty;
        c.s = 0; c.ph = 0; c.sph = 0; c.w = (warp >> 2) - 1; c.wq = warp & 3; c.lane = lane;
        c.osc = g < 3 ? AT_SCALE : 1.f;
        float acc0[64], acc1[64];
        if (g < 3) {
            ln_rows_inplace(sA, c.w * 64 + c.wq * 16, lane, afull, 8, 0);
            fence_proxy_async();
            bar_sync(3 + c.w, 128);
        }
        if (c.w == 0) {
            qkv_tile<true, false, 0>(c, acc0, acc1, afull, 0);
            int i = 1;
            for (; i + 1 < ntile; i += 2) {
                qkv_tile<false, true, 0>(c, acc1, acc0, afull, 0);
                qkv_tile<false, true, 0>(c, acc0, acc1, afull, 0);
            }
            if (i < ntile) { qkv_tile<false, true, 0>(c, acc1, acc0, afull, 0); qkv_drain(c, acc1); }
            else qkv_drain(c, acc0);
        } else {
            qkv_tile<true, false, 1>(c, acc0, acc1, afull, 0);
            int i = 1;
            for (; i + 1 < ntile; i += 2) {
                qkv_tile<false, true, 1>(c, acc1, acc0, afull, 0);
                qkv_tile<false, true, 1>(c, acc0, acc1, afull, 0);
            }
            if (i < ntile) { qkv_tile<false, true, 1>(c, acc1, acc0, afull, 0); qkv_drain(c, acc1); }
            else qkv_drain(c, acc0);
        }
    }
}
constexpr int AT_KST = 2, AT_VST = 2;
constexpr int AT_TILE = 128 * 128 * 2;
constexpr int AT_SMEM = (3 + AT_KST + AT_VST) * AT_TILE + 1024 + 256;
constexpr float AT_SMALL = 9.5367431640625e-07f;
constexpr float AT_BIG = 1073741824.f;

struct PrefetchList { const void* ptr[5]; uint32_t bytes[5]; float* colsum; const bf16* qkv; };
constexpr int AT_PFD = 4;
constexpr int AT_WPF = 10;

struct AttnSched { ulonglong2 e[160]; };
#define attn_get_tile(t, head, qt) attn_get_tile_(my_list, (t), (head), (qt))
__device__ __forceinline__ bool attn_get_tile_(const ulonglong2& list, int t, int& head, int& qt) {
    if (t >= (int)(list.y >> 48)) return false;
    const int e = (int)((t < 4 ? list.x >> (16 * t) : list.y >> (16 * (t - 4))) & 0xffff);
    head = e >> 4; qt = e & 15;
    return true;
}

__device__ __forceinline__ void attn_qk(float (&S)[64], uint64_t dq, uint64_t dk) {
    #pragma unroll
    for (int k = 0; k < 8; k++) {
        const uint32_t off = (k >> 2) * 16384 + (k & 3) * 32;
        wgmma_ss_n128<0, 0>(S, desc_add(dq, off), desc_add(dk, off), k > 0);
    }
}
__device__ __forceinline__ void attn_pv(float (&O)[64], uint32_t (&P)[32], uint64_t dv, int acc) {
    #pragma unroll
    for (int k = 0; k < 8; k++)
        wgmma_rs_n128<1>(O, P[4 * k], P[4 * k + 1], P[4 * k + 2], P[4 * k + 3], desc_add(dv, k * 2048), k > 0 ? 1 : acc);
}
__device__ __forceinline__ float quad_max(float v) {
    v = fmaxf(v, __shfl_xor_sync(0xffffffffu, v, 1));
    return fmaxf(v, __shfl_xor_sync(0xffffffffu, v, 2));
}
__device__ __forceinline__ float quad_sum(float v) {
    v += __shfl_xor_sync(0xffffffffu, v, 1);
    return v + __shfl_xor_sync(0xffffffffu, v, 2);
}
__device__ __forceinline__ void attn_rowmax(const float (&S)[64], float& mx0, float& mx1) {
    float a0 = fmaxf(S[0], S[1]), a1 = fmaxf(S[2], S[3]), b0 = fmaxf(S[4], S[5]), b1 = fmaxf(S[6], S[7]);
    #pragma unroll
    for (int j = 2; j < 16; j += 2) {
        a0 = fmaxf(a0, fmaxf(S[4 * j], S[4 * j + 1]));
        a1 = fmaxf(a1, fmaxf(S[4 * j + 2], S[4 * j + 3]));
        b0 = fmaxf(b0, fmaxf(S[4 * j + 4], S[4 * j + 5]));
        b1 = fmaxf(b1, fmaxf(S[4 * j + 6], S[4 * j + 7]));
    }
    mx0 = quad_max(fmaxf(a0, b0));
    mx1 = quad_max(fmaxf(a1, b1));
}
template<bool ZERO>
__device__ __forceinline__ void attn_exp_pack_(float (&S)[64], float m0, float m1, uint32_t (&P)[32], float& s0, float& s1) {
    float a0 = 0.f, a1 = 0.f, b0 = 0.f, b1 = 0.f;
    #pragma unroll
    for (int j = 0; j < 16; j++) {
        if (!ZERO) { S[4 * j] -= m0; S[4 * j + 1] -= m0; S[4 * j + 2] -= m1; S[4 * j + 3] -= m1; }
        const float e0 = ex2(S[4 * j]), e1 = ex2(S[4 * j + 1]), e2 = ex2(S[4 * j + 2]), e3 = ex2(S[4 * j + 3]);
        a0 += e0; b0 += e1; a1 += e2; b1 += e3;
        P[2 * j] = pack_bf16(e0, e1); P[2 * j + 1] = pack_bf16(e2, e3);
    }
    s0 = a0 + b0; s1 = a1 + b1;
}
__device__ __forceinline__ void attn_exp_pack(float (&S)[64], float m0, float m1, bool zero, uint32_t (&P)[32], float& s0, float& s1) {
    if (zero) attn_exp_pack_<true>(S, m0, m1, P, s0, s1); else attn_exp_pack_<false>(S, m0, m1, P, s0, s1);
}
__device__ __forceinline__ void attn_exp_pack_shift(const float (&S)[64], float d0, float d1, uint32_t (&P)[32], float& s0, float& s1) {
    float a0 = 0.f, a1 = 0.f, b0 = 0.f, b1 = 0.f;
    #pragma unroll
    for (int j = 0; j < 16; j++) {
        const float e0 = ex2(S[4 * j] - d0), e1 = ex2(S[4 * j + 1] - d0), e2 = ex2(S[4 * j + 2] - d1), e3 = ex2(S[4 * j + 3] - d1);
        a0 += e0; b0 += e1; a1 += e2; b1 += e3;
        P[2 * j] = pack_bf16(e0, e1); P[2 * j + 1] = pack_bf16(e2, e3);
    }
    s0 = a0 + b0; s1 = a1 + b1;
}
__global__ void __launch_bounds__(384, 1)
k_attn(const __grid_constant__ CUtensorMap mQKV, const __grid_constant__ CUtensorMap mCtx, const PrefetchList pf,
       const __grid_constant__ AttnSched sched) {
    ulonglong2 my_list = sched.e[blockIdx.x];
    asm volatile("" : "+l"(my_list.x), "+l"(my_list.y));
    extern __shared__ uint8_t smem_raw[];
    const uint32_t sQ = (smem_u32(smem_raw) + 1023) & ~1023u;
    const uint32_t sK = sQ + 2 * AT_TILE, sV = sK + AT_KST * AT_TILE, sO = sV + AT_VST * AT_TILE, sB = sO + AT_TILE;
    const uint32_t qfull = sB, qempty = sB + 16, kfull = sB + 32, kempty = kfull + 8 * AT_KST,
                   vfull = kempty + 8 * AT_KST, vempty = vfull + 8 * AT_VST, ofull = vempty + 8 * AT_VST, oempty = ofull + 16, stepctr = oempty + 16;
    const int warp = __shfl_sync(0xffffffffu, threadIdx.x >> 5, 0);
    const int lane = threadIdx.x & 31;
    if (threadIdx.x == 0) {
        for (int i = 0; i < 2; i++) { mbar_init(qfull + 8 * i, 1); mbar_init(qempty + 8 * i, 2); mbar_init(ofull + 8 * i, 4); mbar_init(oempty + 8 * i, 1); }
        for (int i = 0; i < AT_KST; i++) { mbar_init(kfull + 8 * i, 1); mbar_init(kempty + 8 * i, 2); }
        for (int i = 0; i < AT_VST; i++) { mbar_init(vfull + 8 * i, 1); mbar_init(vempty + 8 * i, 2); }
        asm volatile("st.shared.u32 [%0], %1;" :: "r"(stepctr), "r"(0) : "memory");
        fence_mbar_init();
        prefetch_tmap(&mQKV); prefetch_tmap(&mCtx);
    }
    __syncthreads();
    pdl_launch();
    pdl_wait();

    if (warp < 4) {
        reg_dealloc<40>();
        if (warp == 0) {
          if (elect_one()) {
            int ks = 0, kph = 1, vs = 0, vph = 1;
            int head, qt;
            bool have = attn_get_tile(0, head, qt);
            if (have) {
                mbar_expect_tx(qfull, AT_TILE);
                tma_load_3d(sQ, &mQKV, qfull, 0, head * S_LEN + qt * 128, 0);
            }
            for (int t = 0; have; t++) {
                const int krow = (NH + head) * S_LEN, vrow = (2 * NH + head) * S_LEN;
                int nhead, nqt;
                const bool nxt = attn_get_tile(t + 1, nhead, nqt);
                for (int j = 0; j <= qt + 1; j++) {
                    if (j <= qt) {
                        mbar_wait(kempty + 8 * ks, kph);
                        mbar_expect_tx(kfull + 8 * ks, AT_TILE);
                        tma_load_3d(sK + ks * AT_TILE, &mQKV, kfull + 8 * ks, 0, krow + j * 128, 0);
                        if (++ks == AT_KST) { ks = 0; kph ^= 1; }
                    }
                    if (j > 0) {
                        mbar_wait(vempty + 8 * vs, vph);
                        mbar_expect_tx(vfull + 8 * vs, AT_TILE);
                        tma_load_3d(sV + vs * AT_TILE, &mQKV, vfull + 8 * vs, 0, vrow + (j - 1) * 128, 0);
                        if (++vs == AT_VST) { vs = 0; vph ^= 1; }
                    }
                    if (j == 1 && nxt) {
                        const int b = (t + 1) & 1, u = (t + 1) >> 1;
                        mbar_wait(qempty + 8 * b, (u & 1) ^ 1);
                        mbar_expect_tx(qfull + 8 * b, AT_TILE);
                        tma_load_3d(sQ + b * AT_TILE, &mQKV, qfull + 8 * b, 0, nhead * S_LEN + nqt * 128, 0);
                    }
                }
                have = nxt; head = nhead; qt = nqt;
            }
          }
        } else if (warp == 1) {
            if (elect_one()) {
                int head, qt;
                for (int t = 0; attn_get_tile(t, head, qt); t++) {
                    #pragma unroll
                    for (int w = 0; w < 2; w++) {
                        mbar_wait(ofull + 8 * w, t & 1);
                        fence_proxy_async();
                        const uint32_t src = sO + w * 16384;
                        tma_store_2d(&mCtx, src, head * 128, qt * 128 + w * 64);
                        tma_store_2d(&mCtx, src + 8192, head * 128 + 64, qt * 128 + w * 64);
                        tma_commit();
                    }
                    tma_wait_read<1>(); mbar_arrive(oempty);
                    tma_wait_read<0>(); mbar_arrive(oempty + 8);
                }
                tma_wait_read<0>();
            }
        } else if (warp == 2) {
            for (int c0 = blockIdx.x * 8; c0 < DM + FF; c0 += gridDim.x * 8) {
                const bool first = c0 < DM;
                const bf16* wp = first ? static_cast<const bf16*>(pf.ptr[1]) + c0 : static_cast<const bf16*>(pf.ptr[3]) + (c0 - DM);
                const int ld = first ? DM : FF;
                float a[8] = {0.f, 0.f, 0.f, 0.f, 0.f, 0.f, 0.f, 0.f};
                #pragma unroll 2
                for (int r = lane; r < DM; r += 32) {
                    float f[8]; unpack8(__ldg(reinterpret_cast<const uint4*>(wp + (size_t)r * ld)), f);
                    #pragma unroll
                    for (int e = 0; e < 8; e++) a[e] += f[e];
                }
                #pragma unroll
                for (int e = 0; e < 8; e++) a[e] = warp_sum(a[e]);
                if (lane == 0) {
                    *reinterpret_cast<float4*>(pf.colsum + c0) = make_float4(a[0], a[1], a[2], a[3]);
                    *reinterpret_cast<float4*>(pf.colsum + c0 + 4) = make_float4(a[4], a[5], a[6], a[7]);
                }
            }
            int head, qt, tp = 0, jp = 0, ahead = 0, wstep = -AT_WPF;
            for (int t = 0; attn_get_tile(t, head, qt); t++) wstep += qt + 1;
            bool have = attn_get_tile(0, head, qt);
            auto next_blk = [&]() { if (++jp > qt) { jp = 0; tp++; have = attn_get_tile(tp, head, qt); } };
            while (have && ahead < AT_PFD) { next_blk(); ahead++; }
            for (int st = 0; have; st++) {
                uint32_t cur, spins = 0;
                do {
                    asm volatile("ld.volatile.shared.u32 %0, [%1];" : "=r"(cur) : "r"(stepctr));
                    if ((int)cur >= st) break;
                    __nanosleep(200);
                } while (++spins < 100000u);
                if (head >= NH / 2) {
                    if (qt == 15) {
                        const bf16* kp = pf.qkv + ((size_t)(NH + head) * S_LEN + jp * 128) * HD;
                        const bf16* vp = pf.qkv + ((size_t)(2 * NH + head) * S_LEN + jp * 128) * HD;
                        #pragma unroll
                        for (int r = 0; r < 8; r++) { prefetch_l2(kp + (r * 32 + lane) * 64); prefetch_l2(vp + (r * 32 + lane) * 64); }
                    }
                }
                if (st == wstep) {
                    #pragma unroll 1
                    for (int k = 0; k < 5; k++) {
                        const char* base = reinterpret_cast<const char*>(pf.ptr[k]);
                        for (uint32_t o = (blockIdx.x * 32 + lane) * 128u; o < pf.bytes[k]; o += gridDim.x * 32 * 128u) prefetch_l2(base + o);
                    }
                }
                next_blk();
            }
        } else if (warp == 3) {
            int ks = 0, kph = 0, vs = 0, vph = 0, nstep = 0;
            int head, qt;
            bool have = attn_get_tile(0, head, qt);
            for (int t = 0; have; t++) {
                int nh, nq;
                const bool nxt = attn_get_tile(t + 1, nh, nq);
                const int j0 = (t == 0) ? 0 : 1;
                for (int j = j0; j <= qt + 1; j++) {
                    const bool last = j == qt + 1;
                    if (j == 0) mbar_wait(qfull, 0);
                    if (last && nxt) mbar_wait(qfull + 8 * ((t + 1) & 1), ((t + 1) >> 1) & 1);
                    if (!last || nxt) { mbar_wait(kfull + 8 * ks, kph); if (++ks == AT_KST) { ks = 0; kph ^= 1; } }
                    if (j > 0) { mbar_wait(vfull + 8 * vs, vph); if (++vs == AT_VST) { vs = 0; vph ^= 1; } }
                    bar_sync(1, 288);
                    if (lane == 0) asm volatile("st.volatile.shared.u32 [%0], %1;" :: "r"(stepctr), "r"(++nstep) : "memory");
                    bar_sync(2, 288);
                }
                have = nxt; qt = nq; head = nh;
            }
        }
    } else {
        reg_alloc<232>();
        const int w = (warp >> 2) - 1;
        const int wq = warp & 3;
        const int row0 = w * 64 + wq * 16 + (lane >> 2);
        const int qc = (lane & 3) * 2;
        if (w == 1) bar_arrive(1, 288);
        float O[64], S[64];
        uint32_t P0[32], P1[32];
        int ks = 0, vs = 0;
        int qt = 0;
        float m0 = 0.f, m1 = 0.f, l0 = 0.f, l1 = 0.f;
        bool zm = false;
        const int thr0 = row0 - qc;

        auto mask_diag = [&]() {
            int thr = thr0;
            asm volatile("" : "+r"(thr));
            if (w == 0) {
                #pragma unroll
                for (int j = 0; j < 8; j++) {
                    if (8 * j > thr) S[4 * j] = -INFINITY;
                    if (8 * j + 1 > thr) S[4 * j + 1] = -INFINITY;
                    if (8 * j - 8 > thr) S[4 * j + 2] = -INFINITY;
                    if (8 * j - 7 > thr) S[4 * j + 3] = -INFINITY;
                }
                #pragma unroll
                for (int i = 32; i < 64; i++) S[i] = -INFINITY;
            } else {
                #pragma unroll
                for (int j = 8; j < 16; j++) {
                    if (8 * j > thr) S[4 * j] = -INFINITY;
                    if (8 * j + 1 > thr) S[4 * j + 1] = -INFINITY;
                    if (8 * j - 8 > thr) S[4 * j + 2] = -INFINITY;
                    if (8 * j - 7 > thr) S[4 * j + 3] = -INFINITY;
                }
            }
        };
        auto epilogue = [&](int t, float i0, float i1) {
            const int r = (lane & 7) + ((lane >> 3) & 1) * 8;
            const uint32_t rowaddr = sO + w * 16384 + (wq * 16 + r) * 128;
            mbar_wait(oempty + 8 * w, (t & 1) ^ 1);
            #pragma unroll
            for (int j = 0; j < 16; j += 2) {
                const int cg = j + (lane >> 4);
                const uint32_t a = rowaddr + (cg >> 3) * 8192 + (((cg & 7) ^ (lane & 7)) << 4);
                stmatrix_x4(a, pack_bf16(O[4 * j] * i0, O[4 * j + 1] * i0), pack_bf16(O[4 * j + 2] * i1, O[4 * j + 3] * i1),
                               pack_bf16(O[4 * j + 4] * i0, O[4 * j + 5] * i0), pack_bf16(O[4 * j + 6] * i1, O[4 * j + 7] * i1));
            }
            __syncwarp();
            if (lane == 0) mbar_arrive(ofull + 8 * w);
        };
        const uint32_t sig = (wq == 0 && lane == 0);
        int t = 0, j = 1;
        int nhead, nqt;
        auto step = [&](uint32_t (&Pin)[32], uint32_t (&Pout)[32]) {
            bar_sync(1 + w, 288);
            wgmma_fence();
            attn_qk(S, make_desc(sQ + (t & 1) * AT_TILE + w * 8192, 16, 1024), make_desc(sK + ks * AT_TILE, 16, 1024));
            wgmma_commit();
            attn_pv(O, Pin, make_desc(sV + vs * AT_TILE, 16384, 1024), j != 1);
            wgmma_commit();
            bar_arrive(1 + (w ^ 1), 288);
            wgmma_wait<1>();
            fence_regs(S);
            mbar_arrive_if(kempty + 8 * ks, sig);
            ks ^= 1;
            if (__builtin_expect(j == qt, 0)) {
                mbar_arrive_if(qempty + 8 * (t & 1), sig);
                mask_diag();
            }
            float s0, s1;
            attn_exp_pack(S, m0, m1, zm, Pout, s0, s1);
            const bool bad = __any_sync(0xffffffffu, !(s0 <= AT_BIG && s1 <= AT_BIG));
            if (__builtin_expect(bad, 0)) {
                asm volatile("wgmma.wait_group.sync.aligned 0; // fallback" ::: "memory");
                fence_regs(O);
                float d0, d1;
                attn_rowmax(S, d0, d1);
                d0 = fmaxf(d0, 0.f); d1 = fmaxf(d1, 0.f);
                m0 += d0; m1 += d1; zm = false;
                const float sc0 = ex2(-d0), sc1 = ex2(-d1);
                l0 *= sc0; l1 *= sc1;
                #pragma unroll
                for (int i = 0; i < 16; i++) {
                    O[4 * i] *= sc0; O[4 * i + 1] *= sc0; O[4 * i + 2] *= sc1; O[4 * i + 3] *= sc1;
                }
                attn_exp_pack_shift(S, d0, d1, Pout, s0, s1);
            } else {
                asm volatile("wgmma.wait_group.sync.aligned 0; // common" ::: "memory");
            }
            fence_regs(O); fence_regs(Pin);
            mbar_arrive_if(vempty + 8 * vs, sig);
            vs ^= 1;
            l0 += s0; l1 += s1;
            j++;
        };

        #pragma unroll 1
        for (; attn_get_tile(t, nhead, nqt); t++) {
            const float i0 = __fdividef(1.f, quad_sum(l0)), i1 = __fdividef(1.f, quad_sum(l1));
            bar_sync(1 + w, 288);
            wgmma_fence();
            attn_qk(S, make_desc(sQ + (t & 1) * AT_TILE + w * 8192, 16, 1024), make_desc(sK + ks * AT_TILE, 16, 1024));
            wgmma_commit();
            if (t > 0) { wgmma_fence(); attn_pv(O, P0, make_desc(sV + vs * AT_TILE, 16384, 1024), j != 1); }
            wgmma_commit();
            bar_arrive(1 + (w ^ 1), 288);
            wgmma_wait<1>();
            fence_regs(S);
            qt = nqt;
            mbar_arrive_if(kempty + 8 * ks, sig);
            mbar_arrive_if(qempty + 8 * (t & 1), sig && qt == 0);
            ks ^= 1;
            if (qt == 0) mask_diag();
            {
                m0 = 0.f; m1 = 0.f; zm = true;
                attn_exp_pack_<true>(S, m0, m1, P1, l0, l1);
                const float r0 = quad_sum(l0), r1 = quad_sum(l1);
                const bool unsafe = !(l0 <= AT_BIG) | !(l1 <= AT_BIG) | !(r0 >= AT_SMALL) | !(r1 >= AT_SMALL);
                if (__builtin_expect(__any_sync(0xffffffffu, unsafe), 0)) {
                    attn_rowmax(S, m0, m1);
                    zm = false;
                    attn_exp_pack_shift(S, m0, m1, P1, l0, l1);
                }
            }
            wgmma_wait<0>();
            fence_regs(O); fence_regs(P0);
            if (t > 0) {
                mbar_arrive_if(vempty + 8 * vs, sig);
                vs ^= 1;
                epilogue(t - 1, i0, i1);
            }
            j = 1;
            bool inP0 = false;
            while (j <= qt) {
                step(P1, P0);
                if (j > qt) { inP0 = true; break; }
                step(P0, P1);
            }
            if (!inP0) {
                #pragma unroll
                for (int i = 0; i < 32; i++) P0[i] = P1[i];
            }
        }
        if (t > 0) {
            bar_sync(1 + w, 288);
            wgmma_fence();
            attn_pv(O, P0, make_desc(sV + vs * AT_TILE, 16384, 1024), j != 1);
            wgmma_commit();
            bar_arrive(1 + (w ^ 1), 288);
            const float i0 = __fdividef(1.f, quad_sum(l0)), i1 = __fdividef(1.f, quad_sum(l1));
            wgmma_wait<0>();
            fence_regs(O); fence_regs(P0);
            epilogue(t - 1, i0, i1);
        }
    }
}
__device__ __forceinline__ float gelu_half(float h) {
    const float u = h * fmaf(h * h, 8.f * 0.044715f * 0.7978845608028654f, 2.f * 0.7978845608028654f);
    float t;
    asm("tanh.approx.f32 %0, %1;" : "=f"(t) : "f"(u));
    return fmaf(h, t, h);
}
__device__ __forceinline__ float bf_lo(uint32_t u) { return __uint_as_float(u << 16); }
__device__ __forceinline__ float bf_hi(uint32_t u) { return __uint_as_float(u & 0xffff0000u); }
__device__ __forceinline__ void cluster_sync_relaxed() {
    asm volatile("barrier.cluster.arrive.relaxed.aligned;" ::: "memory");
    cluster_wait();
}

constexpr int GO_ST = 4;
constexpr int GO_STAGE = 16384 + 32768;
constexpr int GO_SMEM = GO_ST * GO_STAGE + 32768 + 1024 + 256;

__global__ void __cluster_dims__(2, 1, 1) __launch_bounds__(384, 1)
k_oproj(const __grid_constant__ CUtensorMap mCtx, const __grid_constant__ CUtensorMap mWo, const __grid_constant__ CUtensorMap mH) {
    extern __shared__ uint8_t smem_raw[];
    const uint32_t s0 = (smem_u32(smem_raw) + 1023) & ~1023u;
    const uint32_t sStg = s0 + GO_ST * GO_STAGE, full = sStg + 32768, empty = full + 8 * GO_ST;
    const int warp = __shfl_sync(0xffffffffu, threadIdx.x >> 5, 0);
    const int lane = threadIdx.x & 31;
    const uint32_t rank = cluster_ctarank();
    const int cl = blockIdx.x >> 1;
    const int rowblk = (cl >> 3) * 2 + rank, nh = cl & 1, ks = (cl >> 1) & 3;
    if (warp == 0 && elect_one()) {
        for (int i = 0; i < GO_ST; i++) { mbar_init(full + 8 * i, 1); mbar_init(empty + 8 * i, 4); }
        fence_mbar_init();
        fence_proxy_async();
        prefetch_tmap(&mCtx); prefetch_tmap(&mWo); prefetch_tmap(&mH);
    }
    __syncthreads();
    cluster_sync_relaxed();
    pdl_launch();
    if (warp < 4) {
        reg_dealloc<40>();
        if (warp == 0 && elect_one()) {
            for (int kb = 0; kb < GO_ST; kb++) {
                mbar_expect_tx(full + 8 * kb, GO_STAGE);
                tma_load_3d_mc(s0 + kb * GO_STAGE + 16384 + rank * 16384, &mWo, full + 8 * kb, 0, ks * 1024 + kb * 64, nh * 4 + rank * 2, (uint16_t)3);
            }
            pdl_wait();
            int s = 0, ph = 1;
            for (int kb = 0; kb < 16; kb++) {
                const int k0 = ks * 1024 + kb * 64;
                const uint32_t st = s0 + s * GO_STAGE;
                if (kb >= GO_ST) {
                    mbar_wait(empty + 8 * s, ph);
                    mbar_expect_tx(full + 8 * s, GO_STAGE);
                    tma_load_3d_mc(st + 16384 + rank * 16384, &mWo, full + 8 * s, 0, k0, nh * 4 + rank * 2, (uint16_t)3);
                }
                tma_load_2d(st, &mCtx, full + 8 * s, k0, rowblk * 128);
                if (++s == GO_ST) { s = 0; ph ^= 1; }
            }
            for (int i = 0; i < GO_ST; i++) { mbar_wait(empty + 8 * s, ph); if (++s == GO_ST) { s = 0; ph ^= 1; } }
        }
    } else {
        reg_alloc<232>();
        const int w = (warp >> 2) - 1, wq = warp & 3;
        float accL[64], accH[64];
        int s = 0, ph = 0;
        for (int kb = 0; kb < 16 - GO_ST; kb++) {
            mbar_wait(full + 8 * s, ph);
            const uint32_t st = s0 + s * GO_STAGE;
            const uint64_t dA = make_desc(st + w * 8192, 16, 1024), dB = make_desc(st + 16384, 8192, 1024);
            wgmma_fence();
            #pragma unroll
            for (int k = 0; k < 4; k++) {
                wgmma_ss_n128<0, 1>(accL, desc_add(dA, k * 32), desc_add(dB, k * 2048), (kb | k) != 0);
                wgmma_ss_n128<0, 1>(accH, desc_add(dA, k * 32), desc_add(dB, 16384 + k * 2048), (kb | k) != 0);
            }
            wgmma_commit();
            wgmma_wait<1>();
            if (kb > 0) { const int sp = s == 0 ? GO_ST - 1 : s - 1; if (wq < 2 && lane == 0) mbar_arrive_cta(empty + 8 * sp, wq); }
            if (++s == GO_ST) { s = 0; ph ^= 1; }
        }
        {
            int s2 = s, ph2 = ph;
            #pragma unroll
            for (int i = 0; i < GO_ST; i++) {
                mbar_wait(full + 8 * s2, ph2);
                const uint32_t st = s0 + s2 * GO_STAGE;
                const uint64_t dA = make_desc(st + w * 8192, 16, 1024), dB = make_desc(st + 16384, 8192, 1024);
                wgmma_fence();
                #pragma unroll
                for (int k = 0; k < 4; k++) wgmma_ss_n128<0, 1>(accL, desc_add(dA, k * 32), desc_add(dB, k * 2048), 1);
                if (i == 0) {
                    wgmma_commit();
                    wgmma_wait<1>();
                    const int sp = s == 0 ? GO_ST - 1 : s - 1;
                    if (wq < 2 && lane == 0) mbar_arrive_cta(empty + 8 * sp, wq);
                }
                if (++s2 == GO_ST) { s2 = 0; ph2 ^= 1; }
            }
            wgmma_commit();
        }
        auto high = [&](int i0) {
            wgmma_fence();
            #pragma unroll
            for (int i = i0; i < i0 + 2; i++) {
                int s2 = s + i; if (s2 >= GO_ST) s2 -= GO_ST;
                const uint32_t st = s0 + s2 * GO_STAGE;
                const uint64_t dA = make_desc(st + w * 8192, 16, 1024), dB = make_desc(st + 16384, 8192, 1024);
                #pragma unroll
                for (int k = 0; k < 4; k++) wgmma_ss_n128<0, 1>(accH, desc_add(dA, k * 32), desc_add(dB, 16384 + k * 2048), 1);
            }
            wgmma_commit();
        };
        high(0);
        const int r = (lane & 7) + ((lane >> 3) & 1) * 8;
        auto epi = [&](const float (&a)[64], uint32_t stg, int col0) {
            const uint32_t rowa = stg + (wq * 16 + r) * 128;
            #pragma unroll
            for (int j = 0; j < 16; j += 2) {
                const int cg = j + (lane >> 4);
                stmatrix_x4(rowa + (cg >> 3) * 8192 + (((cg & 7) ^ (lane & 7)) << 4),
                    pack_bf16(a[4 * j], a[4 * j + 1]), pack_bf16(a[4 * j + 2], a[4 * j + 3]),
                    pack_bf16(a[4 * j + 4], a[4 * j + 5]), pack_bf16(a[4 * j + 6], a[4 * j + 7]));
            }
            bar_sync(3 + w, 128);
            if (wq == 0 && elect_one()) {
                fence_proxy_async();
                tma_red_add_2d(&mH, stg + (ks & 1) * 8192, col0 + (ks & 1) * 64, rowblk * 128 + w * 64);
                tma_red_add_2d(&mH, stg + ((ks & 1) ^ 1) * 8192, col0 + ((ks & 1) ^ 1) * 64, rowblk * 128 + w * 64);
                tma_commit();
            }
        };
        wgmma_wait<1>();
        fence_regs(accL);
        epi(accL, sStg + w * 16384, nh * 256);
        high(2);
        wgmma_wait<0>();
        fence_regs(accH);
        if (wq < 2 && lane == 0) {
            for (int i = 0; i < GO_ST; i++) mbar_arrive_cta(empty + 8 * i, wq);
        }
        bar_sync(1, 256);
        epi(accH, s0 + w * 16384, nh * 256 + 128);
        if (wq == 0 && elect_one()) { tma_wait_read<0>(); }
    }
}

constexpr int G1_SMEM = 65536 + 8 * 16384 + 16384 + 1024 + 64 + 512 + 64;

__global__ void __launch_bounds__(384, 1)
k_g1(const __grid_constant__ CUtensorMap mH, const __grid_constant__ CUtensorMap mW1, const __grid_constant__ CUtensorMap mT1,
     float2* __restrict__ stats, const float* __restrict__ cs1, float2* __restrict__ x1stat) {
    extern __shared__ uint8_t smem_raw[];
    const uint32_t sA = (smem_u32(smem_raw) + 1023) & ~1023u;
    const uint32_t sBm = sA + 65536, sStg = sBm + 8 * 16384, full = sStg + 16384, sStat = full + 64;
    const int warp = __shfl_sync(0xffffffffu, threadIdx.x >> 5, 0);
    const int lane = threadIdx.x & 31;
    const int rb = blockIdx.x >> 2, nq = blockIdx.x & 3;
    if (warp == 0 && elect_one()) {
        for (int i = 0; i < 8; i++) mbar_init(full + 8 * i, 1);
        fence_mbar_init();
        fence_proxy_async();
        for (int kb = 0; kb < 8; kb++) {
            mbar_expect_tx(full + 8 * kb, 16384 + 8192);
            if (kb < 4) tma_load_3d(sBm + kb * 16384, &mW1, full + 8 * kb, 0, kb * 64, nq * 2);
        }
        prefetch_tmap(&mH); prefetch_tmap(&mT1);
    }
    __syncthreads();
    pdl_launch();
    if (warp < 4) {
        if (warp == 0 && elect_one()) {
            pdl_wait();
            for (int kb = 0; kb < 8; kb++) {
                tma_load_2d(sA + kb * 8192, &mH, full + 8 * kb, kb * 64, rb * 64);
                if (kb >= 2 && kb < 6) tma_load_3d(sBm + (kb + 2) * 16384, &mW1, full + 8 * (kb + 2), 0, (kb + 2) * 64, nq * 2);
            }
        }
    } else {
        const int w = (warp >> 2) - 1, wq = warp & 3;
        pdl_wait();
        float cs[16];
        #pragma unroll
        for (int j = 0; j < 8; j++) {
            const float2 t = __ldcg(reinterpret_cast<const float2*>(cs1 + nq * 128 + w * 64 + j * 8 + (lane & 3) * 2));
            cs[2 * j] = t.x; cs[2 * j + 1] = t.y;
        }
        const int srow = (warp - 4) * 8 + (lane >> 2);
        uint32_t soff[2];
        #pragma unroll
        for (int i = 0; i < 2; i++) soff[i] = sA + srow * 128 + ((((lane & 3) * 2 + i) ^ (srow & 7)) << 4);
        float sm0 = 0.f, sm1 = 0.f, sq0 = 0.f, sq1 = 0.f, shift = 0.f;
        float acc[32];
        const uint64_t dA = make_desc(sA, 16, 1024);
        #pragma unroll
        for (int kb = 0; kb < 8; kb++) {
            mbar_wait(full + 8 * kb, 0);
            wgmma_fence();
            const uint64_t dB = make_desc(sBm + kb * 16384 + w * 8192, 8192, 1024);
            #pragma unroll
            for (int k = 0; k < 4; k++) wgmma_ss_n64<0, 1>(acc, desc_add(dA, kb * 8192 + k * 32), desc_add(dB, k * 2048), (kb | k) != 0);
            wgmma_commit();
            const uint4 v0 = lds128(soff[0] + kb * 8192), v1 = lds128(soff[1] + kb * 8192);
            if (kb == 0) shift = __shfl_sync(0xffffffffu, __uint_as_float(v0.x << 16), lane & ~3);
            float f0[8], f1[8]; unpack8(v0, f0); unpack8(v1, f1);
            #pragma unroll
            for (int e = 0; e < 8; e++) {
                const float a = f0[e] - shift, b = f1[e] - shift;
                sm0 += a; sm1 += b; sq0 = fmaf(a, a, sq0); sq1 = fmaf(b, b, sq1);
            }
        }
        {
            float sm = sm0 + sm1, sq = sq0 + sq1;
            sm += __shfl_xor_sync(0xffffffffu, sm, 1); sq += __shfl_xor_sync(0xffffffffu, sq, 1);
            sm += __shfl_xor_sync(0xffffffffu, sm, 2); sq += __shfl_xor_sync(0xffffffffu, sq, 2);
            const float dm = sm * (1.f / DM);
            const float var = fmaxf(sq * (1.f / DM) - dm * dm, 0.f), mean = dm + shift;
            const float rstd = rsqrtf(var + LN_EPS);
            const float sc = 0.5f * rstd * rsqrtf(var * rstd * rstd + LN_EPS);
            if ((lane & 3) == 0) {
                asm volatile("st.shared.v2.f32 [%0], {%1, %2};" :: "r"(sStat + srow * 8), "f"(mean), "f"(sc) : "memory");
                if (nq == 0) { stats[rb * 64 + srow] = make_float2(mean, rstd); x1stat[rb * 64 + srow] = make_float2(0.f, 0.f); }
            }
        }
        bar_sync(1, 256);
        float mean0, sc0, mean1, sc1;
        asm volatile("ld.shared.v2.f32 {%0, %1}, [%2];" : "=f"(mean0), "=f"(sc0) : "r"(sStat + (wq * 16 + (lane >> 2)) * 8));
        asm volatile("ld.shared.v2.f32 {%0, %1}, [%2];" : "=f"(mean1), "=f"(sc1) : "r"(sStat + (wq * 16 + (lane >> 2) + 8) * 8));
        wgmma_wait<0>();
        fence_regs(acc);
        #pragma unroll
        for (int j = 0; j < 8; j++) {
            acc[4 * j]     = gelu_half(fmaf(-mean0, cs[2 * j],     acc[4 * j])     * sc0);
            acc[4 * j + 1] = gelu_half(fmaf(-mean0, cs[2 * j + 1], acc[4 * j + 1]) * sc0);
            acc[4 * j + 2] = gelu_half(fmaf(-mean1, cs[2 * j],     acc[4 * j + 2]) * sc1);
            acc[4 * j + 3] = gelu_half(fmaf(-mean1, cs[2 * j + 1], acc[4 * j + 3]) * sc1);
        }
        const int r = (lane & 7) + ((lane >> 3) & 1) * 8;
        const uint32_t rowa = sStg + w * 8192 + (wq * 16 + r) * 128;
        #pragma unroll
        for (int j = 0; j < 8; j += 2) {
            const int cg = j + (lane >> 4);
            stmatrix_x4(rowa + ((cg ^ (lane & 7)) << 4),
                pack_bf16(acc[4 * j], acc[4 * j + 1]), pack_bf16(acc[4 * j + 2], acc[4 * j + 3]),
                pack_bf16(acc[4 * j + 4], acc[4 * j + 5]), pack_bf16(acc[4 * j + 6], acc[4 * j + 7]));
        }
        bar_sync(3 + w, 128);
        if (wq == 0 && elect_one()) {
            fence_proxy_async();
            tma_store_2d(&mT1, sStg + w * 8192, nq * 128 + w * 64, rb * 64);
            tma_commit();
            tma_wait_read<0>();
        }
    }
}

constexpr int GS_ST = 4;
constexpr int GS_STAGE = 32768 + 16384;
constexpr int GS_SMEM = GS_ST * GS_STAGE + 16384 + 1024 + 256;

__global__ void __cluster_dims__(2, 1, 1) __launch_bounds__(384, 1)
k_g2(const __grid_constant__ CUtensorMap mA, const __grid_constant__ CUtensorMap mW, const __grid_constant__ CUtensorMap mOut,
     const __grid_constant__ CUtensorMap mBase,
     const bf16* __restrict__ h, const float2* __restrict__ stats, float2* __restrict__ x1stat) {
    extern __shared__ uint8_t smem_raw[];
    const uint32_t s0 = (smem_u32(smem_raw) + 1023) & ~1023u;
    const uint32_t sStg = s0 + GS_ST * GS_STAGE, full = sStg + 16384;
    const int warp = __shfl_sync(0xffffffffu, threadIdx.x >> 5, 0);
    const int lane = threadIdx.x & 31;
    const uint32_t rank = cluster_ctarank();
    const int rb = blockIdx.x >> 3, nt = blockIdx.x & 7;
    if (warp == 0 && elect_one()) {
        for (int i = 0; i < GS_ST; i++) mbar_init(full + 8 * i, 1);
        fence_mbar_init();
        fence_proxy_async();
        for (int kb = 0; kb < GS_ST; kb++) {
            mbar_expect_tx(full + 8 * kb, GS_STAGE);
            tma_load_2d(s0 + kb * GS_STAGE + 32768, &mW, full + 8 * kb, nt * 64, kb * 128);
        }
        prefetch_tmap(&mA); prefetch_tmap(&mOut);
    }
    __syncthreads();
    cluster_sync_relaxed();
    pdl_launch();
    if (warp < 4) {
        if (warp == 0 && elect_one()) {
            pdl_wait();
            for (int kb = 0; kb < GS_ST; kb++) {
                const int shift = kb == 0 ? -1 : (kb == 1 ? 1 : (kb == 2 ? -2 : 2));
                tma_load_3d_mc(s0 + kb * GS_STAGE + rank * 16384, &mA, full + 8 * kb, 0, rb * 128 + rank * 64 + shift, kb * 2, (uint16_t)3);
            }
        }
    } else {
        const int w = (warp >> 2) - 1, wq = warp & 3;
        const int row0 = rb * 128 + w * 64 + wq * 16 + (lane >> 2), col0 = nt * 64 + (lane & 3) * 2;
        uint32_t ra[16];
        float2 st0, st1;
        float acc[32];
        #pragma unroll
        for (int kb = 0; kb < GS_ST; kb++) {
            mbar_wait(full + 8 * kb, 0);
            const uint32_t st = s0 + kb * GS_STAGE;
            const uint64_t dA = make_desc(st + w * 16384, 16, 1024), dB = make_desc(st + 32768, 8192, 1024);
            wgmma_fence();
            #pragma unroll
            for (int k = 0; k < 8; k++)
                wgmma_ss_n64<0, 1>(acc, desc_add(dA, (k >> 2) * 8192 + (k & 3) * 32), desc_add(dB, k * 2048), (kb | k) != 0);
            wgmma_commit();
            #pragma unroll
            for (int j = 2 * kb; j < 2 * kb + 2; j++) {
                ra[2 * j] = __ldcg(reinterpret_cast<const uint32_t*>(h + (size_t)row0 * DM + col0 + j * 8));
                ra[2 * j + 1] = __ldcg(reinterpret_cast<const uint32_t*>(h + (size_t)(row0 + 8) * DM + col0 + j * 8));
            }
            if (kb == 0) { st0 = __ldcg(stats + row0); st1 = __ldcg(stats + row0 + 8); }
        }
        wgmma_wait<0>();
        fence_regs(acc);
        #pragma unroll
        for (int j = 0; j < 8; j++) {
            acc[4 * j]     += (bf_lo(ra[2 * j]) - st0.x) * st0.y;     acc[4 * j + 1] += (bf_hi(ra[2 * j]) - st0.x) * st0.y;
            acc[4 * j + 2] += (bf_lo(ra[2 * j + 1]) - st1.x) * st1.y; acc[4 * j + 3] += (bf_hi(ra[2 * j + 1]) - st1.x) * st1.y;
        }
        const int r = (lane & 7) + ((lane >> 3) & 1) * 8;
        const uint32_t rowa = sStg + w * 8192 + (wq * 16 + r) * 128;
        #pragma unroll
        for (int j = 0; j < 8; j += 2) {
            const int cg = j + (lane >> 4);
            stmatrix_x4(rowa + ((cg ^ (lane & 7)) << 4),
                pack_bf16(acc[4 * j], acc[4 * j + 1]), pack_bf16(acc[4 * j + 2], acc[4 * j + 3]),
                pack_bf16(acc[4 * j + 4], acc[4 * j + 5]), pack_bf16(acc[4 * j + 6], acc[4 * j + 7]));
        }
        bar_sync(1, 256);
        const uint32_t rowb = s0 + w * 8192 + (wq * 16 + r) * 128;
        #pragma unroll
        for (int j = 0; j < 8; j += 2) {
            const int cg = j + (lane >> 4);
            stmatrix_x4(rowb + ((cg ^ (lane & 7)) << 4),
                pack_bf16(acc[4 * j] + bf_lo(ra[2 * j]), acc[4 * j + 1] + bf_hi(ra[2 * j])),
                pack_bf16(acc[4 * j + 2] + bf_lo(ra[2 * j + 1]), acc[4 * j + 3] + bf_hi(ra[2 * j + 1])),
                pack_bf16(acc[4 * j + 4] + bf_lo(ra[2 * j + 2]), acc[4 * j + 5] + bf_hi(ra[2 * j + 2])),
                pack_bf16(acc[4 * j + 6] + bf_lo(ra[2 * j + 3]), acc[4 * j + 7] + bf_hi(ra[2 * j + 3])));
        }
        float a0 = 0.f, q0 = 0.f, a1 = 0.f, q1 = 0.f;
        #pragma unroll
        for (int j = 0; j < 8; j++) {
            a0 += acc[4 * j] + acc[4 * j + 1]; q0 = fmaf(acc[4 * j], acc[4 * j], fmaf(acc[4 * j + 1], acc[4 * j + 1], q0));
            a1 += acc[4 * j + 2] + acc[4 * j + 3]; q1 = fmaf(acc[4 * j + 2], acc[4 * j + 2], fmaf(acc[4 * j + 3], acc[4 * j + 3], q1));
        }
        a0 = quad_sum(a0); q0 = quad_sum(q0); a1 = quad_sum(a1); q1 = quad_sum(q1);
        if ((lane & 3) == 0) {
            atomicAdd(&x1stat[row0].x, a0); atomicAdd(&x1stat[row0].y, q0);
            atomicAdd(&x1stat[row0 + 8].x, a1); atomicAdd(&x1stat[row0 + 8].y, q1);
        }
        bar_sync(3 + w, 128);
        if (wq == 0 && elect_one()) {
            fence_proxy_async();
            tma_store_2d(&mOut, sStg + w * 8192, nt * 64, rb * 128 + w * 64);
            tma_store_2d(&mBase, s0 + w * 8192, nt * 64, rb * 128 + w * 64);
            tma_commit();
            tma_wait_read<0>();
        }
    }
}

constexpr int ML_ST = 4;
constexpr int ML_SMEM = 131072 + ML_ST * 16384 + 32768 + 1024 + 256 + 896;

__global__ void __cluster_dims__(2, 1, 1) __launch_bounds__(384, 1)
k_mlp(const __grid_constant__ CUtensorMap mX1, const __grid_constant__ CUtensorMap mW3, const __grid_constant__ CUtensorMap mW4,
      bf16* __restrict__ out, const float* __restrict__ cs3, const float2* __restrict__ x1stat) {
    extern __shared__ uint8_t smem_raw[];
    const uint32_t sA = (smem_u32(smem_raw) + 1023) & ~1023u;
    const uint32_t sBst = sA + 131072, sU = sBst + ML_ST * 16384, full = sU + 32768, empty = full + 8 * ML_ST, afull = empty + 8 * ML_ST, rfull = afull + 64, rempty = rfull + 32, sCs = rempty + 32;
    const int warp = __shfl_sync(0xffffffffu, threadIdx.x >> 5, 0);
    const int lane = threadIdx.x & 31;
    const uint32_t rank = cluster_ctarank();
    const int cl = blockIdx.x >> 1;
    const int rb = (cl >> 3) * 2 + rank, nt = cl & 7;
    const int ncol = nt * 224;
    if (warp == 0 && elect_one()) {
        for (int i = 0; i < ML_ST; i++) { mbar_init(full + 8 * i, 1); mbar_init(empty + 8 * i, 4); }
        for (int i = 0; i < 8; i++) mbar_init(afull + 8 * i, 1);
        for (int i = 0; i < 4; i++) { mbar_init(rfull + 8 * i, 4); mbar_init(rempty + 8 * i, 1); }
        fence_mbar_init();
        fence_proxy_async();
        prefetch_tmap(&mX1); prefetch_tmap(&mW3); prefetch_tmap(&mW4);
    }
    __syncthreads();
    cluster_sync_relaxed();
    pdl_launch();
    if (warp < 4) {
        reg_dealloc<40>();
        if (warp == 0 && elect_one()) {
            auto load_w = [&](int i, int s) {
                mbar_expect_tx(full + 8 * s, 16384);
                const uint32_t dst = sBst + s * 16384 + rank * 8192;
                if (i < 16) tma_load_2d_mc(dst, &mW3, full + 8 * s, ncol + (i >> 3) * 128 + rank * 64, (i & 7) * 64, (uint16_t)3);
                else        tma_load_2d_mc(dst, &mW4, full + 8 * s, ((i - 16) >> 2) * 128 + rank * 64, ncol + (i & 3) * 64, (uint16_t)3);
            };
            for (int i = 0; i < ML_ST; i++) load_w(i, i);
            pdl_wait();
            auto load_a = [&](int c) {
                mbar_expect_tx(afull + 8 * c, 16384);
                tma_load_2d(sA + c * 16384, &mX1, afull + 8 * c, c * 64, rb * 128);
            };
            for (int c = 0; c < 4; c++) load_a(c);
            int s = 0, ph = 0;
            for (int i = ML_ST; i < 32; i++) {
                mbar_wait(empty + 8 * s, ph);
                load_w(i, s);
                if (i < 8) load_a(i);
                if (++s == ML_ST) { s = 0; ph ^= 1; }
            }
            for (int i = 0; i < ML_ST; i++) { mbar_wait(empty + 8 * s, ph); if (++s == ML_ST) { s = 0; ph ^= 1; } }
        } else if (warp == 1 || warp == 2) {
            const int w = warp - 1;
            #pragma unroll 1
            for (int t = 0; t < 4; t++) {
                const int b = t & 1;
                mbar_wait(rfull + 8 * (2 * w + b), t >> 1);
                const uint32_t stg = sA + 32768 + b * 32768 + w * 16384;
                bf16* dst = out + (size_t)(rb * 128 + w * 64 + (lane >> 3)) * DM + t * 128 + (lane & 7) * 8;
                #pragma unroll 4
                for (int it = 0; it < 32; it++) {
                    const int c = (it + nt * 4) & 31;
                    const int row = (c & 15) * 4 + (lane >> 3), ch = c >> 4;
                    const uint4 v = lds128(stg + ch * 8192 + row * 128 + (((lane & 7) ^ (row & 7)) << 4));
                    asm volatile("red.global.add.noftz.v4.bf16x2 [%0], {%1, %2, %3, %4};"
                        :: "l"(dst + (size_t)((c & 15) * 4) * DM + ch * 64), "r"(v.x), "r"(v.y), "r"(v.z), "r"(v.w) : "memory");
                }
                __syncwarp();
                if (lane == 0) mbar_arrive(rempty + 8 * (2 * w + b));
            }
        }
    } else {
        reg_alloc<232>();
        const int w = (warp >> 2) - 1, wq = warp & 3;
        float sc0, sc1, mean0, mean1;
        pdl_wait();
        {
            const int ct = threadIdx.x - 128;
            if (ct < 224) { const float v = __ldcg(cs3 + ncol + ct); asm volatile("st.shared.f32 [%0], %1;" :: "r"(sCs + 4 * ct), "f"(v) : "memory"); }
            const int row0 = rb * 128 + w * 64 + wq * 16 + (lane >> 2);
            const float2 s0 = __ldcg(x1stat + row0), s1 = __ldcg(x1stat + row0 + 8);
            mean0 = s0.x * (1.f / DM); mean1 = s1.x * (1.f / DM);
            sc0 = 0.5f * rsqrtf(fmaxf(s0.y * (1.f / DM) - mean0 * mean0, 0.f) + LN_EPS);
            sc1 = 0.5f * rsqrtf(fmaxf(s1.y * (1.f / DM) - mean1 * mean1, 0.f) + LN_EPS);
            bar_sync(1, 256);
        }
        int s = 0, ph = 0;
        const int r = (lane & 7) + ((lane >> 3) & 1) * 8;
        const uint32_t rowoff = w * 8192 + (wq * 16 + r) * 128;
        auto release = [&](int stage) { if (wq < 2 && lane == 0) mbar_arrive_cta(empty + 8 * stage, wq); };
        auto advance = [&]() { if (++s == ML_ST) { s = 0; ph ^= 1; } };
        float accA[64], accB[64];
        const uint64_t dU01 = make_desc(sU + w * 8192, 16, 1024), dU23 = make_desc(sA + w * 8192, 16, 1024);
        auto mma2 = [&](float (&cur)[64], int kb) {
            mbar_wait(full + 8 * s, ph);
            const uint64_t dB = make_desc(sBst + s * 16384, 8192, 1024);
            const uint64_t dU = desc_add(kb < 2 ? dU01 : dU23, (kb & 1) * 16384);
            wgmma_fence();
            #pragma unroll
            for (int k = 0; k < (kb == 3 ? 2 : 4); k++)
                wgmma_ss_n128<0, 1>(cur, desc_add(dU, k * 32), desc_add(dB, k * 2048), (kb | k) != 0);
            wgmma_commit();
            advance();
        };
        auto prev_stage = [&](int back) { int q = s - back; return q < 0 ? q + ML_ST : q; };
        {
            float acc1[48];
            float (&acc0)[64] = accB;
            const uint64_t dA = make_desc(sA + w * 8192, 16, 1024);
            const uint32_t csa = sCs + (lane & 3) * 8;
            auto ldcs = [&](int col) { float2 v; asm volatile("ld.shared.v2.f32 {%0, %1}, [%2];" : "=f"(v.x), "=f"(v.y) : "r"(csa + col * 4)); return v; };
            auto act = [&](const float* a, int col, uint32_t dst, int cg) {
                const float2 c0 = ldcs(col), c1 = ldcs(col + 8);
                stmatrix_x4(dst + rowoff + (((cg & 7) ^ (lane & 7)) << 4),
                    pack_bf16(gelu_half(fmaf(-mean0, c0.x, a[0]) * sc0), gelu_half(fmaf(-mean0, c0.y, a[1]) * sc0)),
                    pack_bf16(gelu_half(fmaf(-mean1, c0.x, a[2]) * sc1), gelu_half(fmaf(-mean1, c0.y, a[3]) * sc1)),
                    pack_bf16(gelu_half(fmaf(-mean0, c1.x, a[4]) * sc0), gelu_half(fmaf(-mean0, c1.y, a[5]) * sc0)),
                    pack_bf16(gelu_half(fmaf(-mean1, c1.x, a[6]) * sc1), gelu_half(fmaf(-mean1, c1.y, a[7]) * sc1)));
            };
            #pragma unroll
            for (int i = 0; i < 16; i++) {
                const int t = i >> 3, kb = i & 7;
                    if (t == 0) mbar_wait(afull + 8 * kb, 0);
                mbar_wait(full + 8 * s, ph);
                const uint64_t dB = make_desc(sBst + s * 16384, 8192, 1024);
                wgmma_fence();
                #pragma unroll
                for (int k = 0; k < 4; k++) {
                    if (t == 0) wgmma_ss_n128<0, 1>(acc0, desc_add(dA, kb * 16384 + k * 32), desc_add(dB, k * 2048), (kb | k) != 0);
                    else        wgmma_ss_n96<0, 1>(acc1, desc_add(dA, kb * 16384 + k * 32), desc_add(dB, k * 2048), (kb | k) != 0);
                }
                wgmma_commit();
                wgmma_wait<1>();
                    if (i > 0) release(s == 0 ? ML_ST - 1 : s - 1);
                advance();
                if (t == 1) {
                    if (kb == 0) fence_regs(acc0);
                    const int cg = 2 * kb + (lane >> 4);
                    act(&acc0[8 * kb], 16 * kb, sU + (kb >> 2) * 16384, cg);
                }
            }
            wgmma_wait<0>();
            fence_regs(acc1);
            release(prev_stage(1));
            fence_proxy_async();
            bar_sync(3 + w, 128);
            mma2(accA, 0); mma2(accA, 1);
            #pragma unroll
            for (int j = 0; j < 6; j++) {
                const int cg = 2 * j + (lane >> 4);
                act(&acc1[8 * j], 128 + 16 * j, sA + (j >> 2) * 16384, cg);
            }
            fence_proxy_async();
            bar_sync(3 + w, 128);
        }
        {
            auto epi_slices = [&](const float (&a)[64], int t, int j0, int j1) {
                const uint32_t stg = sA + 32768 + (t & 1) * 32768 + w * 16384 + (wq * 16 + r) * 128;
                #pragma unroll
                for (int j2 = j0; j2 < j1; j2++) {
                    const int j = 2 * j2, cg = j + (lane >> 4);
                    stmatrix_x4(stg + (cg >> 3) * 8192 + (((cg & 7) ^ (lane & 7)) << 4),
                        pack_bf16(a[4 * j], a[4 * j + 1]), pack_bf16(a[4 * j + 2], a[4 * j + 3]),
                        pack_bf16(a[4 * j + 4], a[4 * j + 5]), pack_bf16(a[4 * j + 6], a[4 * j + 7]));
                }
            };
            auto epi_issue = [&](int t) {
                __syncwarp();
                if (lane == 0) mbar_arrive(rfull + 8 * (2 * w + (t & 1)));
            };
            wgmma_wait<0>();
            release(prev_stage(2)); release(prev_stage(1));
            mma2(accA, 2); mma2(accA, 3);
            auto next_tile = [&](float (&cur)[64], float (&prev)[64], int t) {
                mma2(cur, 0);
                wgmma_wait<1>();
                fence_regs(prev);
                release(prev_stage(3)); release(prev_stage(2));
                mma2(cur, 1);
                if (t == 3) mbar_wait(rempty + 8 * (2 * w), 0);
                epi_slices(prev, t - 1, 0, 8);
                epi_issue(t - 1);
                wgmma_wait<0>();
                release(prev_stage(2)); release(prev_stage(1));
                mma2(cur, 2); mma2(cur, 3);
            };
            next_tile(accB, accA, 1);
            next_tile(accA, accB, 2);
            next_tile(accB, accA, 3);
            wgmma_wait<0>();
            fence_regs(accB);
            release(prev_stage(2)); release(prev_stage(1));
            mbar_wait(rempty + 8 * (2 * w + 1), 0);
            epi_slices(accB, 3, 0, 8);
            epi_issue(3);
        }
    }
}
__device__ __align__(1024) bf16  g_qkv[3 * NH * S_LEN * HD];
__device__ __align__(1024) bf16  g_ctx[S_LEN * NH * HD];
__device__ __align__(1024) bf16  g_h[S_LEN * DM];
__device__ __align__(1024) float2 g_stats[S_LEN];
__device__ __align__(1024) float g_colsum[DM + FF];
__device__ __align__(1024) float2 g_x1stat[S_LEN];
__device__ __align__(1024) bf16  g_t1[S_LEN * DM];
__device__ __align__(1024) bf16  g_x1[S_LEN * DM];

typedef CUresult (*EncodeTiledFn)(CUtensorMap*, CUtensorMapDataType, cuuint32_t, void*, const cuuint64_t*, const cuuint64_t*,
                                  const cuuint32_t*, const cuuint32_t*, CUtensorMapInterleave, CUtensorMapSwizzle,
                                  CUtensorMapL2promotion, CUtensorMapFloatOOBfill);
static EncodeTiledFn g_encode = nullptr;

static CUtensorMap make_map(const void* ptr, int rank, const uint64_t* dims, const uint64_t* strides, const uint32_t* box,
                            CUtensorMapSwizzle sw = CU_TENSOR_MAP_SWIZZLE_128B) {
    const CUtensorMapDataType dt = CU_TENSOR_MAP_DATA_TYPE_BFLOAT16;
    CUtensorMap m;
    cuuint64_t d[3], st[2]; cuuint32_t b[3], es[3] = {1, 1, 1};
    for (int i = 0; i < rank; i++) { d[i] = dims[i]; b[i] = box[i]; }
    for (int i = 0; i < rank - 1; i++) st[i] = strides[i];
    g_encode(&m, dt, rank, (void*)ptr, d, st, b, es, CU_TENSOR_MAP_INTERLEAVE_NONE, sw,
             CU_TENSOR_MAP_L2_PROMOTION_L2_128B, CU_TENSOR_MAP_FLOAT_OOB_FILL_NONE);
    return m;
}
static CUtensorMap map2d(const void* p, uint64_t cols, uint64_t rows, uint32_t box_cols, uint32_t box_rows) {
    uint64_t d[2] = {cols, rows}, s[1] = {cols * 2}; uint32_t b[2] = {box_cols, box_rows};
    return make_map(p, 2, d, s, b);
}
static CUtensorMap map3d(const void* p, uint64_t cols, uint64_t rows, uint32_t box_rows, uint32_t nchunks) {
    uint64_t d[3] = {64, rows, cols / 64}, s[2] = {cols * 2, 128}; uint32_t b[3] = {64, box_rows, nchunks};
    return make_map(p, 3, d, s, b);
}

template<typename... KArgs, typename... Args>
static void launch(void (*kern)(KArgs...), int grid, int smem, cudaStream_t st, bool pdl, Args... args) {
    cudaLaunchConfig_t cfg = {};
    cfg.gridDim = dim3(grid); cfg.blockDim = dim3(384); cfg.dynamicSmemBytes = smem; cfg.stream = st;
    cudaLaunchAttribute at[1];
    at[0].id = cudaLaunchAttributeProgrammaticStreamSerialization;
    at[0].val.programmaticStreamSerializationAllowed = 1;
    cfg.attrs = at; cfg.numAttrs = pdl ? 1 : 0;
    cudaLaunchKernelEx(&cfg, kern, KArgs(args)...);
}

#define USE_PDL 1

struct Plan {
    CUtensorMap mX, mC, mWq, mWk, mWv, mQkvOut, mQkvIn, mCtxOut, mCtxIn, mWo, mH, mW1, mT1out, mT1in, mW2, mX1out, mX1in, mW3, mW4, mOut;
    bf16 *qkv, *ctx, *t1, *x1, *h, *out; float2 *stats, *x1stat; float* colsum;
    AttnSched sched; int attn_grid;
};

static void build_sched(Plan& p, int sms) {
    AttnSched& sc = p.sched;
    for (int i = 0; i < 160; i++) { sc.e[i].x = 0; sc.e[i].y = 0; }
    auto add = [&](int b, int h, int q) {
        const int n = (int)(sc.e[b].y >> 48);
        const unsigned long long v = (unsigned long long)(h * 16 + q);
        if (n < 4) sc.e[b].x |= v << (16 * n); else sc.e[b].y |= v << (16 * (n - 4));
        sc.e[b].y += 1ull << 48;
    };
    if (sms == 132) {
        p.attn_grid = 132;
        int b = 0;
        for (int h = 0; h < 8; h++) for (int i = 0; i < 8; i++) { add(b, h, 15 - i); add(b, h, i); b++; }
        for (int h = 8; h < 16; h++) { add(b++, h, 15); for (int i = 0; i < 7; i++) { add(b, h, 14 - i); add(b, h, i); b++; } }
        for (int h = 8; h < 16; h += 2) { add(b, h, 7); add(b, h + 1, 7); b++; }
        b = 64; int r = 0;
        for (int h = 16; h < 25; h++) for (int i = 0; i < 8; i++) {
            if (i == 0 && h < 20) { add(r++, h, 15); continue; }
            add(b, h, 15 - i); add(b, h, i); b++;
        }
        for (int h = 25; h < 32; h++) { add(r++, h, 15); for (int i = 0; i < 7; i++) { add(r, h, 14 - i); add(r, h, i); r++; } }
        for (int h = 25; h < 31; h += 2) { add(r, h, 7); add(r, h + 1, 7); r++; }
        add(r, 31, 7); for (int h = 16; h < 20; h++) add(r, h, 0);
    } else {
        p.attn_grid = sms < 86 ? 86 : (sms > 160 ? 160 : sms);
        for (int q = 0; q < NH * 8; q++) { const int b = q % p.attn_grid; add(b, q >> 3, 15 - (q & 7)); add(b, q >> 3, q & 7); }
    }
}

static void build_plan(Plan& p, void* const* d_in, void* d_out) {
    if (!g_encode) {
        void* fn = nullptr; cudaDriverEntryPointQueryResult qr;
        cudaGetDriverEntryPoint("cuTensorMapEncodeTiled", &fn, cudaEnableDefault, &qr);
        g_encode = (EncodeTiledFn)fn;
        cudaFuncSetAttribute(k_qkv, cudaFuncAttributeMaxDynamicSharedMemorySize, QK_SMEM);
        cudaFuncSetAttribute(k_attn, cudaFuncAttributeMaxDynamicSharedMemorySize, AT_SMEM);
        cudaFuncSetAttribute(k_oproj, cudaFuncAttributeMaxDynamicSharedMemorySize, GO_SMEM);
        cudaFuncSetAttribute(k_g1, cudaFuncAttributeMaxDynamicSharedMemorySize, G1_SMEM);
        cudaFuncSetAttribute(k_g2, cudaFuncAttributeMaxDynamicSharedMemorySize, GS_SMEM);
        cudaFuncSetAttribute(k_mlp, cudaFuncAttributeMaxDynamicSharedMemorySize, ML_SMEM);
    }
    { int dev = 0, sms = 132; cudaGetDevice(&dev); cudaDeviceGetAttribute(&sms, cudaDevAttrMultiProcessorCount, dev); build_sched(p, sms); }
    cudaGetSymbolAddress((void**)&p.qkv, g_qkv); cudaGetSymbolAddress((void**)&p.ctx, g_ctx);
    cudaGetSymbolAddress((void**)&p.h, g_h); cudaGetSymbolAddress((void**)&p.stats, g_stats); cudaGetSymbolAddress((void**)&p.colsum, g_colsum); cudaGetSymbolAddress((void**)&p.x1stat, g_x1stat);
    cudaGetSymbolAddress((void**)&p.t1, g_t1); cudaGetSymbolAddress((void**)&p.x1, g_x1);
    p.mX = map2d(d_in[0], DM, S_LEN, 64, 128);
    p.mC = map2d(d_in[1], DM, S_LEN, 64, 128);
    p.mWq = map2d(d_in[2], NH * HD, DM, 64, 64);
    p.mWk = map2d(d_in[3], NH * HD, DM, 64, 64);
    p.mWv = map2d(d_in[4], NH * HD, DM, 64, 64);
    p.mQkvOut = map2d(p.qkv, HD, 3 * NH * S_LEN, 64, 64);
    p.mQkvIn = map3d(p.qkv, HD, 3 * NH * S_LEN, 128, 2);
    p.mCtxOut = map2d(p.ctx, NH * HD, S_LEN, 64, 64);
    p.mCtxIn = map2d(p.ctx, NH * HD, S_LEN, 64, 128);
    p.mWo = map3d(d_in[5], DM, NH * HD, 64, 2);
    p.mH = map2d(p.h, DM, S_LEN, 64, 64);
    p.mW1 = map3d(d_in[7], DM, DM, 64, 2);
    p.mT1out = map2d(p.t1, DM, S_LEN, 64, 64);
    p.mT1in = map3d(p.t1, DM, S_LEN, 64, 2);
    p.mW2 = map2d(d_in[8], DM, DM, 64, 128);
    p.mX1out = map2d(p.x1, DM, S_LEN, 64, 64);
    p.mX1in = map2d(p.x1, DM, S_LEN, 64, 128);
    p.mW3 = map2d(d_in[9], FF, DM, 64, 64);
    p.mW4 = map2d(d_in[10], DM, FF, 64, 64);
    p.mOut = map2d(d_out, DM, S_LEN, 64, 64);
    p.out = (bf16*)d_out;
}

static void run_stage(const Plan& p, int stage, void* const* d_in, cudaStream_t st, bool pdl) {
    switch (stage) {
    case 0: launch(k_qkv, 128, QK_SMEM, st, false, p.mX, p.mC, p.mWq, p.mWk, p.mWv, p.mQkvOut, (const bf16*)d_in[0], p.h, (const bf16*)d_in[2], (const bf16*)d_in[3], (const bf16*)d_in[4]); break;
    case 1: {
        PrefetchList pf;
        pf.ptr[0] = d_in[5]; pf.bytes[0] = NH * HD * DM * 2;
        pf.ptr[1] = d_in[7]; pf.bytes[1] = DM * DM * 2;
        pf.ptr[2] = d_in[8]; pf.bytes[2] = DM * DM * 2;
        pf.ptr[3] = d_in[9]; pf.bytes[3] = DM * FF * 2;
        pf.ptr[4] = d_in[10]; pf.bytes[4] = DM * FF * 2;
        pf.colsum = p.colsum; pf.qkv = p.qkv;
        launch(k_attn, p.attn_grid, AT_SMEM, st, pdl, p.mQkvIn, p.mCtxOut, pf, p.sched); break; }
    case 2: launch(k_oproj, 128, GO_SMEM, st, pdl, p.mCtxIn, p.mWo, p.mH); break;
    case 3: launch(k_g1, 128, G1_SMEM, st, pdl, p.mH, p.mW1, p.mT1out, p.stats, (const float*)p.colsum, p.x1stat); break;
    case 4: launch(k_g2, 128, GS_SMEM, st, pdl, p.mT1in, p.mW2, p.mX1out, p.mOut, (const bf16*)p.h, (const float2*)p.stats, p.x1stat); break;
    case 5: launch(k_mlp, 128, ML_SMEM, st, pdl, p.mX1in, p.mW3, p.mW4, p.out, (const float*)(p.colsum + DM), (const float2*)p.x1stat); break;
    }
}

constexpr int NUM_STAGES = 6;
extern "C" void kernel_launch(void* const* d_in, const int* in_sizes, int n_in, void* d_out, int out_size) {
    Plan p;
    build_plan(p, d_in, d_out);
    cudaStream_t st = cudaStreamPerThread;
    for (int s = 0; s < NUM_STAGES; s++) run_stage(p, s, d_in, st, USE_PDL);
}
```
